```python
import torch

def _softmax(x, axis=-1):
    return torch.softmax(x, dim=axis)
def _gelu(x):
    return torch.nn.functional.gelu(x, approximate="tanh")
def _silu(x):
    return torch.nn.functional.silu(x)
def _sigmoid(x):
    return torch.sigmoid(x)
def _layernorm(x, axis=-1, eps=1e-5):
    m = x.mean(dim=axis, keepdim=True)
    v = x.var(dim=axis, keepdim=True, unbiased=False)
    return (x - m) / torch.sqrt(v + eps)
def _scatter_add(tgt, idx, src, axis=0):
    return tgt.clone().index_add_(axis, idx, src)
def _segment_sum(src, seg, n):
    out = torch.zeros((n,) + src.shape[1:], dtype=src.dtype)
    return out.index_add_(0, seg, src)
def _pad(x, pw):
    flat = tuple(v for pair in reversed(pw) for v in pair)
    return torch.nn.functional.pad(x, flat)

kernel_name = 'sequential_preLN__linear_kernel_hedgehog__dense_activation_gelu__prompt'

def setup_inputs():

    _w = (lambda a: (lambda t: t.to(torch.bfloat16) if t.is_floating_point() else t)(torch.as_tensor(a)))
    def _A_setup():
        B, S, D, H = 1, 2048, 576, 32
        Dh = D // H
        return {
            "x": _w((lambda *s: torch.randn(*s, dtype=torch.bfloat16) * 0.05)(B, S, D)),
            "wqkv": _w((lambda *s: torch.randn(*s, dtype=torch.bfloat16) * 0.2)(D, 3 * D)),
            "w_phi": _w((lambda *s: torch.randn(*s, dtype=torch.bfloat16) * 0.2)(H, Dh, Dh) * (Dh ** -0.5)),
            "wo": _w((lambda *s: torch.randn(*s, dtype=torch.bfloat16) * 0.05)(D, D)),
        }
    _A_in = _A_setup()

    def _B_setup():
        B, S, D, F = 1, 2048, 576, 4608
        return {
            "x": _w((lambda *s: torch.randn(*s, dtype=torch.bfloat16) * 0.05)(B, S, D)),
            "w1": _w((lambda *s: torch.randn(*s, dtype=torch.bfloat16) * 3.2)(D, F) * (D ** -0.5)),
            "b1": _w((lambda *s: torch.randn(*s, dtype=torch.bfloat16) * 0.1)(F) * 0.01),
            "w2": _w((lambda *s: torch.randn(*s, dtype=torch.bfloat16) * 0.1)(F, D) * (F ** -0.5)),
            "b2": _w((lambda *s: torch.randn(*s, dtype=torch.bfloat16) * 0.1)(D) * 0.01),
        }
    _B_in = _B_setup()

    return {
        "A_x": _A_in["x"],
        "A_wqkv": _A_in["wqkv"],
        "A_w_phi": _A_in["w_phi"],
        "A_wo": _A_in["wo"],
        "B_x": _B_in["x"],
        "B_w1": _B_in["w1"],
        "B_b1": _B_in["b1"],
        "B_w2": _B_in["w2"],
        "B_b2": _B_in["b2"],
    }

def reference(A_x, A_wqkv, A_w_phi, A_wo, B_x, B_w1, B_b1, B_w2, B_b2):
    def _A_ref(x, wqkv, w_phi, wo):
        B, S, D = x.shape
        H = 32; Dh = D // H
        qkv = (lambda x, *d: x.permute(*d))((x @ wqkv).reshape(B, S, 3, H, Dh), 2, 0, 3, 1, 4)
        q, k, v = qkv[0], qkv[1], qkv[2]
        pq = torch.einsum("bhsd,hdf->bhsf", q, w_phi)
        pk = torch.einsum("bhsd,hdf->bhsf", k, w_phi)
        phi_q = torch.concatenate([_softmax(pq, axis=-1), _softmax(-pq, axis=-1)], axis=-1)
        phi_k = torch.concatenate([_softmax(pk, axis=-1), _softmax(-pk, axis=-1)], axis=-1)
        kv = torch.einsum("bhsf,bhsd->bhfd", phi_k, v)
        z  = torch.einsum("bhsf->bhf", phi_k)
        num = torch.einsum("bhqf,bhfd->bhqd", phi_q, kv)
        den = torch.einsum("bhqf,bhf->bhq", phi_q, z)[..., None] + 1e-6
        o = num / den
        return (lambda x, *d: x.permute(*d))(o, 0, 2, 1, 3).reshape(B, S, D) @ wo

    def _B_ref(x, w1, b1, w2, b2):
        h = torch.einsum("bsd,df->bsf", x, w1) + b1
        h = _gelu(h)
        return torch.einsum("bsf,fd->bsd", h, w2) + b2

    x = A_x
    h = x + _A_ref(_layernorm(x, axis=-1), A_wqkv, A_w_phi, A_wo)
    h2 = h + _B_ref(_layernorm(h, axis=-1), B_w1, B_b1, B_w2, B_b2)
    return h2
```

```cpp
#include <cuda_runtime.h>
#include <cuda.h>
#include <cuda_bf16.h>
#include <stdint.h>
#include <type_traits>

namespace {

constexpr int S_ = 2048, D_ = 576, F_ = 4608;
constexpr int NSLOT = 8, SLOT_BYTES = 12288;
constexpr uint32_t OFF_X    = NSLOT * SLOT_BYTES;
constexpr uint32_t OFF_PHI  = OFF_X;
constexpr uint32_t OFF_V    = OFF_X + 65536;
constexpr uint32_t OFF_WPHI = OFF_X + 90112;
constexpr uint32_t OFF_KVB  = OFF_X + 101632;
constexpr uint32_t OFF_B1   = OFF_X + 131072;
constexpr uint32_t OFF_BAR  = OFF_B1 + 2304;
constexpr uint32_t SMEM_BYTES = OFF_BAR + 144 + 256;
constexpr uint32_t SB = 1024;
constexpr int SPIN_LIMIT = 1 << 21;

enum { BAR_INIT = 1, BAR_PREP = 2, BAR_KVIN = 3, BAR_KVOUT = 4, BAR_KVB = 5 };

struct Params {
  CUtensorMap tq64, tq32, to64, to32, tw1, tw2, tout;
  const __nv_bfloat16 *x, *wqkv, *wphi, *wo, *w1, *b1, *w2, *b2;
  __nv_bfloat16* out;
};

__device__ uint4    g_o[16 * 8 * 36 * 32];
__device__ uint4    g_h[16 * 8 * 36 * 32];
__device__ float2   g_stats[S_ * 8];
__device__ float4   g_kv[2 * 8 * 720];
__device__ unsigned g_cnt_kv[8 * 32];
__device__ unsigned g_cnt_o[128 * 32];
__device__ unsigned g_cnt_h[128 * 32];
__device__ unsigned g_epoch[128];
#define TS(i)
#define TS_DUMP()

__device__ __forceinline__ void mbar_init(uint32_t bar, uint32_t cnt) { asm volatile("mbarrier.init.shared::cta.b64 [%0], %1;" ::"r"(bar), "r"(cnt)); }
__device__ __forceinline__ void mbar_expect_tx(uint32_t bar, uint32_t bytes) { asm volatile("mbarrier.arrive.expect_tx.shared::cta.b64 _, [%0], %1;" ::"r"(bar), "r"(bytes) : "memory"); }
__device__ __forceinline__ void mbar_arrive(uint32_t bar) { asm volatile("mbarrier.arrive.shared::cta.b64 _, [%0];" ::"r"(bar) : "memory"); }
__device__ __forceinline__ void mbar_wait(uint32_t bar, uint32_t parity) {
  asm volatile(
      "{\n.reg .pred p;\n.reg .u32 n;\nmov.u32 n, 0;\n"
      "WAIT_%=:\n"
      "mbarrier.try_wait.parity.shared::cta.b64 p, [%0], %1;\n"
      "@p bra DONE_%=;\n"
      "add.u32 n, n, 1;\n"
      "setp.lt.u32 p, n, %2;\n"
      "@p bra WAIT_%=;\n"
      "DONE_%=:\n}\n" ::"r"(bar), "r"(parity), "n"(SPIN_LIMIT) : "memory");
}
__device__ __forceinline__ void bar_sync(int id, int n) { asm volatile("bar.sync %0, %1;" ::"r"(id), "r"(n) : "memory"); }
__device__ __forceinline__ void bar_arrive(int id, int n) { asm volatile("bar.arrive %0, %1;" ::"r"(id), "r"(n) : "memory"); }
__device__ __forceinline__ void fence_async_smem() { asm volatile("fence.proxy.async.shared::cta;" ::: "memory"); }
__device__ __forceinline__ void tma2d(uint32_t dst, const CUtensorMap* m, int c0, int c1, uint32_t bar) {
  asm volatile("cp.async.bulk.tensor.2d.shared::cluster.global.mbarrier::complete_tx::bytes [%0], [%1, {%3, %4}], [%2];" ::"r"(dst), "l"(m), "r"(bar), "r"(c0), "r"(c1) : "memory");
}
__device__ __forceinline__ void tma5d(uint32_t dst, const CUtensorMap* m, int c0, int c4, uint32_t bar) {
  asm volatile("cp.async.bulk.tensor.5d.shared::cluster.global.mbarrier::complete_tx::bytes [%0], [%1, {%3, %5, %5, %5, %4}], [%2];" ::"r"(dst), "l"(m), "r"(bar), "r"(c0), "r"(c4), "r"(0) : "memory");
}
__device__ __forceinline__ void l2_prefetch(const void* p, uint32_t bytes) { asm volatile("cp.async.bulk.prefetch.L2.global [%0], %1;" ::"l"(p), "r"(bytes) : "memory"); }
__device__ __forceinline__ void wg_fence() { asm volatile("wgmma.fence.sync.aligned;" ::: "memory"); }
__device__ __forceinline__ void wg_commit() { asm volatile("wgmma.commit_group.sync.aligned;" ::: "memory"); }
template <int N> __device__ __forceinline__ void wg_wait() { asm volatile("wgmma.wait_group.sync.aligned %0;" ::"n"(N) : "memory"); }
template <int N> __device__ __forceinline__ void pin(float (&d)[N]) {
#pragma unroll
  for (int i = 0; i < N; i++) asm volatile("" : "+f"(d[i])::"memory");
}
__device__ __forceinline__ uint64_t make_desc(uint32_t addr, uint32_t lbo, uint32_t sbo, uint32_t swz) {
  return (uint64_t)(((addr & 0x3FFFF) >> 4) | ((lbo >> 4) << 16)) | ((uint64_t)((sbo >> 4) | (swz << 30)) << 32);
}
__device__ __forceinline__ uint32_t pack2(float lo, float hi) { uint32_t r; asm("cvt.rn.bf16x2.f32 %0, %1, %2;" : "=r"(r) : "f"(hi), "f"(lo)); return r; }
__device__ __forceinline__ float bf_lo(uint32_t v) { return __uint_as_float(v << 16); }
__device__ __forceinline__ float bf_hi(uint32_t v) { return __uint_as_float(v & 0xffff0000u); }
__device__ __forceinline__ uint32_t hsub2(uint32_t a, uint32_t b) { uint32_t r; asm("sub.rn.bf16x2 %0, %1, %2;" : "=r"(r) : "r"(a), "r"(b)); return r; }
__device__ __forceinline__ float ex2(float x) { float r; asm("ex2.approx.ftz.f32 %0, %1;" : "=f"(r) : "f"(x)); return r; }
__device__ __forceinline__ float rcp(float x) { float r; asm("rcp.approx.ftz.f32 %0, %1;" : "=f"(r) : "f"(x)); return r; }
__device__ __forceinline__ float tanh_(float x) { float r; asm("tanh.approx.f32 %0, %1;" : "=f"(r) : "f"(x)); return r; }
__device__ __forceinline__ void mma16816(float (&d)[4], uint32_t a0, uint32_t a1, uint32_t a2, uint32_t a3, uint32_t b0, uint32_t b1) {
  asm("mma.sync.aligned.m16n8k16.row.col.f32.bf16.bf16.f32 {%0,%1,%2,%3}, {%4,%5,%6,%7}, {%8,%9}, {%0,%1,%2,%3};"
      : "+f"(d[0]), "+f"(d[1]), "+f"(d[2]), "+f"(d[3]) : "r"(a0), "r"(a1), "r"(a2), "r"(a3), "r"(b0), "r"(b1));
}
__device__ __forceinline__ void mma1688(float (&d)[4], uint32_t a0, uint32_t a1, uint32_t b0) {
  asm("mma.sync.aligned.m16n8k8.row.col.f32.bf16.bf16.f32 {%0,%1,%2,%3}, {%4,%5}, {%6}, {%0,%1,%2,%3};"
      : "+f"(d[0]), "+f"(d[1]), "+f"(d[2]), "+f"(d[3]) : "r"(a0), "r"(a1), "r"(b0));
}
__device__ __forceinline__ void sts32(uint32_t a, uint32_t v) { asm volatile("st.shared.b32 [%0], %1;" ::"r"(a), "r"(v) : "memory"); }
__device__ __forceinline__ void sts64(uint32_t a, uint32_t v0, uint32_t v1) { asm volatile("st.shared.v2.b32 [%0], {%1,%2};" ::"r"(a), "r"(v0), "r"(v1) : "memory"); }
__device__ __forceinline__ void sts128(uint32_t a, uint32_t v0, uint32_t v1, uint32_t v2, uint32_t v3) { asm volatile("st.shared.v4.b32 [%0], {%1,%2,%3,%4};" ::"r"(a), "r"(v0), "r"(v1), "r"(v2), "r"(v3) : "memory"); }
__device__ __forceinline__ void lds128(uint32_t a, uint32_t& v0, uint32_t& v1, uint32_t& v2, uint32_t& v3) { asm volatile("ld.shared.v4.b32 {%0,%1,%2,%3}, [%4];" : "=r"(v0), "=r"(v1), "=r"(v2), "=r"(v3) : "r"(a) : "memory"); }
__device__ __forceinline__ void ldg128_nc(const void* p, uint32_t& v0, uint32_t& v1, uint32_t& v2, uint32_t& v3) { asm volatile("ld.global.nc.L1::no_allocate.v4.b32 {%0,%1,%2,%3}, [%4];" : "=r"(v0), "=r"(v1), "=r"(v2), "=r"(v3) : "l"(p)); }
__device__ __forceinline__ void ldg128_cg(const void* p, uint32_t& v0, uint32_t& v1, uint32_t& v2, uint32_t& v3) { asm volatile("ld.global.cg.v4.b32 {%0,%1,%2,%3}, [%4];" : "=r"(v0), "=r"(v1), "=r"(v2), "=r"(v3) : "l"(p) : "memory"); }
__device__ __forceinline__ uint32_t ldg32_nc(const void* p) { uint32_t v; asm volatile("ld.global.nc.b32 %0, [%1];" : "=r"(v) : "l"(p)); return v; }
__device__ __forceinline__ void stg128(void* p, uint32_t v0, uint32_t v1, uint32_t v2, uint32_t v3) { asm volatile("st.global.v4.b32 [%0], {%1,%2,%3,%4};" ::"l"(p), "r"(v0), "r"(v1), "r"(v2), "r"(v3) : "memory"); }
__device__ __forceinline__ void stg64(void* p, uint32_t v0, uint32_t v1) { asm volatile("st.global.v2.b32 [%0], {%1,%2};" ::"l"(p), "r"(v0), "r"(v1) : "memory"); }
__device__ __forceinline__ void stg32(void* p, uint32_t v) { asm volatile("st.global.b32 [%0], %1;" ::"l"(p), "r"(v) : "memory"); }
__device__ __forceinline__ void signal(unsigned* c) { asm volatile("red.release.gpu.global.add.u32 [%0], 1;" ::"l"(c) : "memory"); }
__device__ __forceinline__ void poll(const unsigned* c, unsigned target) {
  unsigned v; int n = 0;
  do { asm volatile("ld.acquire.gpu.global.u32 %0, [%1];" : "=r"(v) : "l"(c) : "memory"); } while ((int)(v - target) < 0 && ++n < SPIN_LIMIT);
}

template <uint32_t OFF, uint32_t HI, int SCALE_D>
__device__ __forceinline__ void wgmma_rs(float (&d)[16], uint32_t a0, uint32_t a1, uint32_t a2, uint32_t a3, uint32_t lo) {
  asm volatile("{\n.reg .pred p;\n.reg .b32 t;\n.reg .b64 bd;\nsetp.ne.b32 p, %23, 0;\nadd.u32 t, %20, %21;\nmov.b64 bd, {t, %22};\n"
    "wgmma.mma_async.sync.aligned.m64n32k16.f32.bf16.bf16 {%0, %1, %2, %3, %4, %5, %6, %7, %8, %9, %10, %11, %12, %13, %14, %15}, {%16, %17, %18, %19}, bd, p, 1, 1, 1;\n}\n"
    : "+f"(d[0]), "+f"(d[1]), "+f"(d[2]), "+f"(d[3]), "+f"(d[4]), "+f"(d[5]), "+f"(d[6]), "+f"(d[7]), "+f"(d[8]), "+f"(d[9]), "+f"(d[10]), "+f"(d[11]), "+f"(d[12]), "+f"(d[13]), "+f"(d[14]), "+f"(d[15])
    : "r"(a0), "r"(a1), "r"(a2), "r"(a3), "r"(lo), "n"(OFF), "n"(HI), "n"(SCALE_D));
}
template <uint32_t OFF, uint32_t HI, int SCALE_D>
__device__ __forceinline__ void wgmma_rs(float (&d)[20], uint32_t a0, uint32_t a1, uint32_t a2, uint32_t a3, uint32_t lo) {
  asm volatile("{\n.reg .pred p;\n.reg .b32 t;\n.reg .b64 bd;\nsetp.ne.b32 p, %27, 0;\nadd.u32 t, %24, %25;\nmov.b64 bd, {t, %26};\n"
    "wgmma.mma_async.sync.aligned.m64n40k16.f32.bf16.bf16 {%0, %1, %2, %3, %4, %5, %6, %7, %8, %9, %10, %11, %12, %13, %14, %15, %16, %17, %18, %19}, {%20, %21, %22, %23}, bd, p, 1, 1, 1;\n}\n"
    : "+f"(d[0]), "+f"(d[1]), "+f"(d[2]), "+f"(d[3]), "+f"(d[4]), "+f"(d[5]), "+f"(d[6]), "+f"(d[7]), "+f"(d[8]), "+f"(d[9]), "+f"(d[10]), "+f"(d[11]), "+f"(d[12]), "+f"(d[13]), "+f"(d[14]), "+f"(d[15]), "+f"(d[16]), "+f"(d[17]), "+f"(d[18]), "+f"(d[19])
    : "r"(a0), "r"(a1), "r"(a2), "r"(a3), "r"(lo), "n"(OFF), "n"(HI), "n"(SCALE_D));
}
template <uint32_t OFF, uint32_t HI, int SCALE_D>
__device__ __forceinline__ void wgmma_rs(float (&d)[32], uint32_t a0, uint32_t a1, uint32_t a2, uint32_t a3, uint32_t lo) {
  asm volatile("{\n.reg .pred p;\n.reg .b32 t;\n.reg .b64 bd;\nsetp.ne.b32 p, %39, 0;\nadd.u32 t, %36, %37;\nmov.b64 bd, {t, %38};\n"
    "wgmma.mma_async.sync.aligned.m64n64k16.f32.bf16.bf16 {%0, %1, %2, %3, %4, %5, %6, %7, %8, %9, %10, %11, %12, %13, %14, %15, %16, %17, %18, %19, %20, %21, %22, %23, %24, %25, %26, %27, %28, %29, %30, %31}, {%32, %33, %34, %35}, bd, p, 1, 1, 1;\n}\n"
    : "+f"(d[0]), "+f"(d[1]), "+f"(d[2]), "+f"(d[3]), "+f"(d[4]), "+f"(d[5]), "+f"(d[6]), "+f"(d[7]), "+f"(d[8]), "+f"(d[9]), "+f"(d[10]), "+f"(d[11]), "+f"(d[12]), "+f"(d[13]), "+f"(d[14]), "+f"(d[15]), "+f"(d[16]), "+f"(d[17]), "+f"(d[18]), "+f"(d[19]), "+f"(d[20]), "+f"(d[21]), "+f"(d[22]), "+f"(d[23]), "+f"(d[24]), "+f"(d[25]), "+f"(d[26]), "+f"(d[27]), "+f"(d[28]), "+f"(d[29]), "+f"(d[30]), "+f"(d[31])
    : "r"(a0), "r"(a1), "r"(a2), "r"(a3), "r"(lo), "n"(OFF), "n"(HI), "n"(SCALE_D));
}
template <uint32_t OFF, uint32_t HI, int SCALE_D>
__device__ __forceinline__ void wgmma_rs(float (&d)[36], uint32_t a0, uint32_t a1, uint32_t a2, uint32_t a3, uint32_t lo) {
  asm volatile("{\n.reg .pred p;\n.reg .b32 t;\n.reg .b64 bd;\nsetp.ne.b32 p, %43, 0;\nadd.u32 t, %40, %41;\nmov.b64 bd, {t, %42};\n"
    "wgmma.mma_async.sync.aligned.m64n72k16.f32.bf16.bf16 {%0, %1, %2, %3, %4, %5, %6, %7, %8, %9, %10, %11, %12, %13, %14, %15, %16, %17, %18, %19, %20, %21, %22, %23, %24, %25, %26, %27, %28, %29, %30, %31, %32, %33, %34, %35}, {%36, %37, %38, %39}, bd, p, 1, 1, 1;\n}\n"
    : "+f"(d[0]), "+f"(d[1]), "+f"(d[2]), "+f"(d[3]), "+f"(d[4]), "+f"(d[5]), "+f"(d[6]), "+f"(d[7]), "+f"(d[8]), "+f"(d[9]), "+f"(d[10]), "+f"(d[11]), "+f"(d[12]), "+f"(d[13]), "+f"(d[14]), "+f"(d[15]), "+f"(d[16]), "+f"(d[17]), "+f"(d[18]), "+f"(d[19]), "+f"(d[20]), "+f"(d[21]), "+f"(d[22]), "+f"(d[23]), "+f"(d[24]), "+f"(d[25]), "+f"(d[26]), "+f"(d[27]), "+f"(d[28]), "+f"(d[29]), "+f"(d[30]), "+f"(d[31]), "+f"(d[32]), "+f"(d[33]), "+f"(d[34]), "+f"(d[35])
    : "r"(a0), "r"(a1), "r"(a2), "r"(a3), "r"(lo), "n"(OFF), "n"(HI), "n"(SCALE_D));
}
template <uint32_t OFF, uint32_t HI, int SCALE_D>
__device__ __forceinline__ void wgmma_rs(float (&d)[44], uint32_t a0, uint32_t a1, uint32_t a2, uint32_t a3, uint32_t lo) {
  asm volatile("{\n.reg .pred p;\n.reg .b32 t;\n.reg .b64 bd;\nsetp.ne.b32 p, %51, 0;\nadd.u32 t, %48, %49;\nmov.b64 bd, {t, %50};\n"
    "wgmma.mma_async.sync.aligned.m64n88k16.f32.bf16.bf16 {%0, %1, %2, %3, %4, %5, %6, %7, %8, %9, %10, %11, %12, %13, %14, %15, %16, %17, %18, %19, %20, %21, %22, %23, %24, %25, %26, %27, %28, %29, %30, %31, %32, %33, %34, %35, %36, %37, %38, %39, %40, %41, %42, %43}, {%44, %45, %46, %47}, bd, p, 1, 1, 1;\n}\n"
    : "+f"(d[0]), "+f"(d[1]), "+f"(d[2]), "+f"(d[3]), "+f"(d[4]), "+f"(d[5]), "+f"(d[6]), "+f"(d[7]), "+f"(d[8]), "+f"(d[9]), "+f"(d[10]), "+f"(d[11]), "+f"(d[12]), "+f"(d[13]), "+f"(d[14]), "+f"(d[15]), "+f"(d[16]), "+f"(d[17]), "+f"(d[18]), "+f"(d[19]), "+f"(d[20]), "+f"(d[21]), "+f"(d[22]), "+f"(d[23]), "+f"(d[24]), "+f"(d[25]), "+f"(d[26]), "+f"(d[27]), "+f"(d[28]), "+f"(d[29]), "+f"(d[30]), "+f"(d[31]), "+f"(d[32]), "+f"(d[33]), "+f"(d[34]), "+f"(d[35]), "+f"(d[36]), "+f"(d[37]), "+f"(d[38]), "+f"(d[39]), "+f"(d[40]), "+f"(d[41]), "+f"(d[42]), "+f"(d[43])
    : "r"(a0), "r"(a1), "r"(a2), "r"(a3), "r"(lo), "n"(OFF), "n"(HI), "n"(SCALE_D));
}
__device__ __forceinline__ void wgmma_ss_tt(float (&d)[12], uint64_t adesc, uint64_t bdesc, int scale_d) {
  asm volatile("{\n.reg .pred p;\nsetp.ne.b32 p, %14, 0;\n"
    "wgmma.mma_async.sync.aligned.m64n24k16.f32.bf16.bf16 {%0, %1, %2, %3, %4, %5, %6, %7, %8, %9, %10, %11}, %12, %13, p, 1, 1, 1, 1;\n}\n"
    : "+f"(d[0]), "+f"(d[1]), "+f"(d[2]), "+f"(d[3]), "+f"(d[4]), "+f"(d[5]), "+f"(d[6]), "+f"(d[7]), "+f"(d[8]), "+f"(d[9]), "+f"(d[10]), "+f"(d[11])
    : "l"(adesc), "l"(bdesc), "r"(scale_d));
}

__host__ __device__ constexpr uint32_t desc_lo(uint32_t addr, uint32_t lbo) { return ((addr & 0x3FFFF) >> 4) | ((lbo >> 4) << 16); }
__host__ __device__ constexpr uint32_t desc_hi(uint32_t sbo, uint32_t swz) { return (sbo >> 4) | (swz << 30); }
template <int I, int N, class F> __device__ __forceinline__ void static_for(F f) {
  if constexpr (I < N) { f(std::integral_constant<int, I>{}); static_for<I + 1, N>(f); }
}

template <int KS, int K0, int ROWB, int NA>
__device__ __forceinline__ void stage_mma(float (&acc)[NA], const uint32_t (&a)[144], uint32_t sb, uint32_t it, uint32_t boff) {
  const uint32_t slot = it & (NSLOT - 1);
  mbar_wait(sb + OFF_BAR + 8 * slot, (it >> 3) & 1);
  wg_fence();
  const uint32_t lo = slot * (SLOT_BYTES >> 4) + boff;
  static_for<0, KS>([&](auto kk) {
    constexpr int k = K0 + kk.value;
    wgmma_rs<desc_lo(SB + kk.value * 16 * ROWB, 16), desc_hi(8 * ROWB, ROWB == 128 ? 1 : 2), k != 0>(acc, a[4 * k], a[4 * k + 1], a[4 * k + 2], a[4 * k + 3], lo);
  });
  wg_commit();
}
template <int KS, int K0, int ROWB, int IT, int NA>
__device__ __forceinline__ void stage_c(float (&acc)[NA], const uint32_t (&a)[144], uint32_t boff) {
  constexpr uint32_t slot = IT & (NSLOT - 1);
  mbar_wait(SB + OFF_BAR + 8 * slot, (IT >> 3) & 1);
  wg_fence();
  static_for<0, KS>([&](auto kk) {
    constexpr int k = K0 + kk.value;
    wgmma_rs<desc_lo(SB + slot * SLOT_BYTES + kk.value * 16 * ROWB, 16), desc_hi(8 * ROWB, ROWB == 128 ? 1 : 2), k != 0>(acc, a[4 * k], a[4 * k + 1], a[4 * k + 2], a[4 * k + 3], boff);
  });
  wg_commit();
}
__device__ __forceinline__ void release(uint32_t sb, uint32_t it, int lane) {
  if (lane == 0) mbar_arrive(sb + OFF_BAR + 64 + 8 * (it & (NSLOT - 1)));
}

template <int HI, int NEG>
__device__ __forceinline__ void softmax18(const float (&p)[36], uint32_t (&w)[9]) {
  constexpr float L2E = NEG ? -1.4426950408889634f : 1.4426950408889634f;
  float m = p[2 * HI];
#pragma unroll
  for (int i = 1; i < 18; i++) { const float v = p[4 * (i >> 1) + 2 * HI + (i & 1)]; m = NEG ? fminf(m, v) : fmaxf(m, v); }
  m *= -L2E;
  float e[18], s = 0.f;
#pragma unroll
  for (int i = 0; i < 18; i++) { e[i] = ex2(fmaf(p[4 * (i >> 1) + 2 * HI + (i & 1)], L2E, m)); s += e[i]; }
  s = rcp(s);
#pragma unroll
  for (int t = 0; t < 9; t++) w[t] = pack2(e[2 * t] * s, e[2 * t + 1] * s);
}
template <int HI, int NEG>
__device__ __forceinline__ void phik_piece(const float (&p)[36], uint32_t rowaddr, int c, int t7) {
  uint32_t w[9];
  softmax18<HI, NEG>(p, w);
  rowaddr += HI * 1024;
  sts128(rowaddr + ((((2 * NEG + 2 * c) & 7) ^ t7) << 4), w[0], w[1], w[2], w[3]);
  sts128(rowaddr + ((((2 * NEG + 1 + 2 * c) & 7) ^ t7) << 4), w[4], w[5], w[6], w[7]);
  sts32(rowaddr + ((((4 + 2 * c) & 7) ^ t7) << 4) + 4 * NEG, w[8]);
}
template <int HI, int NEG>
__device__ __forceinline__ void phiq_piece(const float (&p)[36], uint32_t (&fq)[36]) {
  uint32_t w[9];
  softmax18<HI, NEG>(p, w);
#pragma unroll
  for (int t = 0; t < 8; t++) fq[2 * (8 * NEG + t) + HI] = w[t];
  fq[2 * (16 + NEG) + HI] = w[8];
}

__device__ __forceinline__ void phi_mma0(float (&p)[36], const float (&a32)[16], float rlo, float rhi, uint32_t sb) {
  uint32_t f[8];
#pragma unroll
  for (int j = 0; j < 4; j++) { f[2 * j] = pack2(a32[4 * j] * rlo, a32[4 * j + 1] * rlo); f[2 * j + 1] = pack2(a32[4 * j + 2] * rhi, a32[4 * j + 3] * rhi); }
  wg_fence();
  static_for<0, 2>([&](auto s) { wgmma_rs<desc_lo(SB + OFF_WPHI + s.value * 256, 128), desc_hi(1280, 0), s.value != 0>(p, f[4 * s.value], f[4 * s.value + 1], f[4 * s.value + 2], f[4 * s.value + 3], 0); });
  wg_commit();
}
__device__ __forceinline__ void phi_mma1(float (&p)[36], const float (&a40)[20], float rlo, float rhi, uint32_t sb) {
  uint32_t f[12];
#pragma unroll
  for (int j = 0; j < 5; j++) { f[2 * j] = pack2(a40[4 * j] * rlo, a40[4 * j + 1] * rlo); f[2 * j + 1] = pack2(a40[4 * j + 2] * rhi, a40[4 * j + 3] * rhi); }
  f[10] = 0; f[11] = 0;
  wg_fence();
  static_for<0, 3>([&](auto s) { wgmma_rs<desc_lo(SB + OFF_WPHI + 512 + s.value * 256, 128), desc_hi(1280, 0), 1>(p, f[4 * s.value], f[4 * s.value + 1], f[4 * s.value + 2], f[4 * s.value + 3], 0); });
  wg_commit();
}

__device__ __forceinline__ void store_frag(uint4* base, const uint32_t (&f)[18], int g) {
  uint4* p = base + ((9 * g) >> 1) * 32;
  if (g & 1) {
    stg64(reinterpret_cast<uint2*>(p) + 1, f[0], f[1]);
#pragma unroll
    for (int s = 0; s < 4; s++) stg128(p + (s + 1) * 32, f[2 + 4 * s], f[3 + 4 * s], f[4 + 4 * s], f[5 + 4 * s]);
  } else {
#pragma unroll
    for (int s = 0; s < 4; s++) stg128(p + s * 32, f[4 * s], f[4 * s + 1], f[4 * s + 2], f[4 * s + 3]);
    stg64(p + 4 * 32, f[16], f[17]);
  }
}

__device__ __forceinline__ float gelu(float y) {
  const float t = tanh_(y * fmaf(y * y, 0.035677408136f, 0.797884560803f));
  const float hy = 0.5f * y;
  return fmaf(hy, t, hy);
}
template <int Q>
__device__ __forceinline__ void gelu_chunk(const float (&acc)[32], float rlo, float rhi, uint32_t b1addr, uint32_t& o0, uint32_t& o1, uint32_t& o2, uint32_t& o3) {
  uint32_t b0, b1, b2, b3;
  lds128(b1addr + Q * 64, b0, b1, b2, b3);
  o0 = pack2(gelu(fmaf(acc[8 * Q + 0], rlo, __uint_as_float(b0))), gelu(fmaf(acc[8 * Q + 1], rlo, __uint_as_float(b1))));
  o1 = pack2(gelu(fmaf(acc[8 * Q + 2], rhi, __uint_as_float(b0))), gelu(fmaf(acc[8 * Q + 3], rhi, __uint_as_float(b1))));
  o2 = pack2(gelu(fmaf(acc[8 * Q + 4], rlo, __uint_as_float(b2))), gelu(fmaf(acc[8 * Q + 5], rlo, __uint_as_float(b3))));
  o3 = pack2(gelu(fmaf(acc[8 * Q + 6], rhi, __uint_as_float(b2))), gelu(fmaf(acc[8 * Q + 7], rhi, __uint_as_float(b3))));
}
template <int Q>
__device__ __forceinline__ void gelu_sts(const float (&acc)[32], float rlo, float rhi, uint32_t b1addr, uint32_t dst) {
  uint32_t o0, o1, o2, o3;
  gelu_chunk<Q>(acc, rlo, rhi, b1addr, o0, o1, o2, o3);
  sts128(dst + Q * 512, o0, o1, o2, o3);
}
template <int Q>
__device__ __forceinline__ void out_chunk(const float (&acc)[32], uint32_t rowaddr, int x7) {
  const uint32_t a = rowaddr + (((2 * Q) ^ x7) << 4);
  asm volatile("stmatrix.sync.aligned.m8n8.x4.shared.b16 [%0], {%1,%2,%3,%4};" ::"r"(a),
               "r"(pack2(acc[8 * Q + 0], acc[8 * Q + 1])), "r"(pack2(acc[8 * Q + 2], acc[8 * Q + 3])),
               "r"(pack2(acc[8 * Q + 4], acc[8 * Q + 5])), "r"(pack2(acc[8 * Q + 6], acc[8 * Q + 7])) : "memory");
}
__device__ __forceinline__ void out_send(const CUtensorMap* m, uint32_t src, int col, int row, int lane) {
  fence_async_smem();
  __syncwarp();
  if (lane == 0) {
    asm volatile("cp.reduce.async.bulk.tensor.2d.global.shared::cta.add.tile.bulk_group [%0, {%2, %3}], [%1];" ::"l"(m), "r"(src), "r"(col), "r"(row) : "memory");
    asm volatile("cp.async.bulk.commit_group;" ::: "memory");
  }
}

template <class E>
__device__ __forceinline__ void ffn_head(float (&accX)[32], float (&accY)[32], const uint32_t (&a)[144], uint32_t sb, uint32_t it, int lane, E epi) {
  stage_mma<6, 0, 128>(accX, a, sb, it, 0);
  wg_wait<1>(); pin(accY); release(sb, it - 1, lane);
  stage_mma<6, 6, 128>(accX, a, sb, it + 1, 0);
  epi(std::integral_constant<int, 0>{});
  wg_wait<1>(); release(sb, it, lane);
  stage_mma<6, 12, 128>(accX, a, sb, it + 2, 0);
  epi(std::integral_constant<int, 1>{});
  wg_wait<1>(); release(sb, it + 1, lane);
  stage_mma<6, 18, 128>(accX, a, sb, it + 3, 0);
  epi(std::integral_constant<int, 2>{});
  wg_wait<1>(); release(sb, it + 2, lane);
  stage_mma<6, 24, 128>(accX, a, sb, it + 4, 0);
  epi(std::integral_constant<int, 3>{});
  wg_wait<1>(); release(sb, it + 3, lane);
}
__device__ __forceinline__ void ffn_tail(float (&accX)[32], const uint32_t (&a)[144], uint32_t sb, uint32_t it5, int lane) {
  stage_mma<6, 30, 128>(accX, a, sb, it5, 0);
  wg_wait<1>(); release(sb, it5 - 1, lane);
}

__global__ void __launch_bounds__(384, 1) fused_block_kernel(const __grid_constant__ Params P) {
  extern __shared__ __align__(1024) uint8_t smem_raw[];
  constexpr uint32_t sb = SB;
  const int tid = threadIdx.x, warp = tid >> 5, lane = tid & 31;
  const int blk = blockIdx.x;
  int r, g;
  {
    const int q = blk >> 3, u = q >> 1;
    const int R = (u < 4) ? u : 7 - u;
    const int G = ((u >> 2) << 1) | ((q ^ u) & 1);
    r = 4 * R + ((blk & 7) >> 1);
    g = 2 * G + (blk & 1);
  }
  const int odd = g & 1;

  if (warp >= 8) {
    asm volatile("setmaxnreg.dec.sync.aligned.u32 24;");
    if (warp == 8) {
      if (lane == 0) {
#pragma unroll
        for (int s = 0; s < NSLOT; s++) { mbar_init(sb + OFF_BAR + 8 * s, 1); mbar_init(sb + OFF_BAR + 64 + 8 * s, 8); }
        mbar_init(sb + OFF_BAR + 128, 1);
        asm volatile("fence.mbarrier_init.release.cluster;" ::: "memory");
        fence_async_smem();
      }
      __syncwarp();
      bar_arrive(BAR_INIT, 384);
      if (lane == 0 && (uint32_t)__cvta_generic_to_shared(smem_raw) == sb) {
        uint32_t it = 0;
        auto acquire = [&]() -> uint32_t {
          const uint32_t slot = it & (NSLOT - 1);
          mbar_wait(sb + OFF_BAR + 64 + 8 * slot, ((it >> 3) & 1) ^ 1);
          mbar_expect_tx(sb + OFF_BAR + 8 * slot, SLOT_BYTES);
          it++;
          return slot;
        };
        const int c64 = 72 * g + (odd ? -8 : 32), c32 = 72 * g + (odd ? 40 : 0);
#pragma unroll 1
        for (int p = 0; p < 6; p++) {
          const int sec = (p >= 4) ? 0 : (p / 2 + 1) * D_;
          if ((p + 1) & 2) {
#pragma unroll 1
            for (int s = 0; s < 6; s++) { const uint32_t sl = acquire(); tma5d(sb + sl * SLOT_BYTES, &P.tq64, sec + c64, 3 * s, sb + OFF_BAR + 8 * sl); }
          } else {
#pragma unroll 1
            for (int s = 0; s < 3; s++) { const uint32_t sl = acquire(); tma5d(sb + sl * SLOT_BYTES, &P.tq32, sec + c32, 6 * s, sb + OFF_BAR + 8 * sl); }
          }
        }
#pragma unroll 1
        for (int s = 0; s < 3; s++) {
          uint32_t sl = acquire(); tma2d(sb + sl * SLOT_BYTES, &P.to64, c64, 192 * s, sb + OFF_BAR + 8 * sl);
          sl = acquire(); tma2d(sb + sl * SLOT_BYTES, &P.to64, c64, 192 * s + 96, sb + OFF_BAR + 8 * sl);
          sl = acquire(); tma2d(sb + sl * SLOT_BYTES, &P.to32, c32, 192 * s, sb + OFF_BAR + 8 * sl);
        }
#pragma unroll 1
        for (int p = 0; p < 9; p++)
#pragma unroll 1
          for (int s = 0; s < 6; s++) { const uint32_t sl = acquire(); tma2d(sb + sl * SLOT_BYTES, &P.tw1, D_ * g + 64 * p, 96 * s, sb + OFF_BAR + 8 * sl); }
#pragma unroll 1
        for (int p = 0; p < 9; p++)
#pragma unroll 1
          for (int s = 0; s < 6; s++) { const uint32_t sl = acquire(); tma2d(sb + sl * SLOT_BYTES, &P.tw2, 64 * p, D_ * g + 96 * s, sb + OFF_BAR + 8 * sl); }
      }
    } else {
      const int ht = tid - 288;
      const unsigned ep = *reinterpret_cast<volatile unsigned*>(&g_epoch[blk]);
      if (ht == 0) l2_prefetch(reinterpret_cast<const char*>(P.wqkv) + blk * 15552, 15552);
      for (int i = ht; i < (11520 + 25344) / 16; i += 96) sts128(sb + OFF_WPHI + i * 16, 0, 0, 0, 0);
      for (int i = ht; i < 512; i += 96) sts128(sb + OFF_V + (i >> 7) * 6144 + 4096 + (i & 127) * 16, 0, 0x00003f80u, 0, 0);
      bar_sync(6, 96);
      bar_sync(BAR_INIT, 384);
      {
        const int c40 = odd ? 0 : 32, c32 = odd ? 40 : 0;
        const uint32_t* wp = reinterpret_cast<const uint32_t*>(P.wphi) + g * 648;
        for (int i = ht; i < 648; i += 96) {
          const int col = i / 9, t = i - col * 9, h = col / 18;
          const int kk = (col >= c40 && col < c40 + 40) ? 32 + col - c40 : col - c32;
          sts32(sb + OFF_WPHI + t * 1280 + kk * 16 + 4 * h, ldg32_nc(wp + i));
        }
        const uint32_t* bp = reinterpret_cast<const uint32_t*>(P.b1) + g * 288;
        for (int i = ht; i < 288; i += 96) {
          const uint32_t v = ldg32_nc(bp + i);
          sts64(sb + OFF_B1 + (i >> 3) * 64 + (i & 3) * 16 + ((i >> 2) & 1) * 8, v << 16, v & 0xffff0000u);
        }
      }
      fence_async_smem();
      bar_arrive(BAR_PREP, 352);
      if (ht < 45) g_kv[(((ep + 1) & 1) * 8 + g) * 720 + r * 45 + ht] = make_float4(0.f, 0.f, 0.f, 0.f);
      if (ht == 32) l2_prefetch(reinterpret_cast<const char*>(P.wo) + blk * 5184, 5184);
      if (ht == 33) l2_prefetch(reinterpret_cast<const char*>(P.w1) + blk * 41472, 41472);
      if (ht == 34) l2_prefetch(reinterpret_cast<const char*>(P.w2) + blk * 41472, 41472);
      float4* kv = g_kv + ((ep & 1) * 8 + g) * 720;
      if (warp == 9) {
        bar_sync(BAR_KVOUT, 288);
        if (lane == 0) {
#pragma unroll
          for (int h = 0; h < 4; h++)
            asm volatile("cp.reduce.async.bulk.global.shared::cta.bulk_group.add.f32 [%0], [%1], %2;" ::"l"(kv + h * 180), "r"(sb + OFF_V + h * 6144), "r"(2880) : "memory");
          asm volatile("cp.async.bulk.commit_group;" ::: "memory");
          asm volatile("cp.async.bulk.wait_group 0;" ::: "memory");
          asm volatile("fence.proxy.async.global;" ::: "memory");
          signal(&g_cnt_kv[g * 32]);
          mbar_expect_tx(sb + OFF_BAR + 128, 11520);
          poll(&g_cnt_kv[g * 32], (ep + 1) * 16);
          asm volatile("fence.proxy.async.global;" ::: "memory");
          asm volatile("cp.async.bulk.shared::cluster.global.mbarrier::complete_tx::bytes [%0], [%1], %2, [%3];" ::"r"(sb + OFF_PHI), "l"(kv), "r"(11520), "r"(sb + OFF_BAR + 128) : "memory");
        }
      }
      mbar_wait(sb + OFF_BAR + 128, 0);
#pragma unroll 1
      for (int e = ht; e < 720; e += 96) {
        uint32_t v0, v1, v2, v3;
        lds128(sb + OFF_PHI + e * 16, v0, v1, v2, v3);
        const int row = e / 5, qd = e - row * 5, h = row / 36, f = row - h * 36;
        const uint32_t ra = sb + OFF_KVB + (16 * (f >> 2) + 8 * ((f >> 1) & 1) + 2 * h + (f & 1)) * 16;
        const int n0 = 18 * h + 4 * qd;
        sts32(ra + (n0 >> 3) * 2304 + (n0 & 7) * 2, pack2(__uint_as_float(v0), __uint_as_float(v1)));
        if (qd < 4) {
          const int n1 = n0 + 2;
          sts32(ra + (n1 >> 3) * 2304 + (n1 & 7) * 2, pack2(__uint_as_float(v2), __uint_as_float(v3)));
        } else {
          const uint32_t z = (h & 1) ? pack2(0.f, __uint_as_float(v2)) : pack2(__uint_as_float(v2), 0.f);
          sts128(ra + (9 + (h >> 1)) * 2304, z, z, z, z);
        }
      }
      fence_async_smem();
      bar_arrive(BAR_KVB, 352);
    }
  } else {
    asm volatile("setmaxnreg.inc.sync.aligned.u32 240;");
    TS(0);
    const int c = lane & 3, rq = lane >> 2;
    const int row = r * 128 + warp * 16 + rq;
    uint32_t a[144];
    float rlo, rhi;
    const unsigned ep = *reinterpret_cast<volatile unsigned*>(&g_epoch[blk]);
    {
      uint32_t xl[72], xh[72];
      const uint4* xp = reinterpret_cast<const uint4*>(P.x) + (size_t)row * 72 + c;
#pragma unroll
      for (int b = 0; b < 18; b++) {
        ldg128_nc(xp + 4 * b, xl[4 * b], xl[4 * b + 1], xl[4 * b + 2], xl[4 * b + 3]);
        ldg128_nc(xp + 8 * 72 + 4 * b, xh[4 * b], xh[4 * b + 1], xh[4 * b + 2], xh[4 * b + 3]);
      }
      float sl[4] = {}, sh[4] = {}, dl[2][4] = {}, dh[2][4] = {};
#pragma unroll
      for (int b = 0; b < 18; b++) {
        mma16816(sl, xl[4 * b], xl[4 * b + 1], xl[4 * b + 2], xl[4 * b + 3], 0x3f803f80u, 0x3f803f80u);
        mma16816(sh, xh[4 * b], xh[4 * b + 1], xh[4 * b + 2], xh[4 * b + 3], 0x3f803f80u, 0x3f803f80u);
#pragma unroll
        for (int t = 0; t < 4; t += 2) {
          mma1688(dl[0], xl[4 * b + t], xl[4 * b + t + 1], xl[4 * b + t]);
          mma1688(dl[1], xl[4 * b + t], xl[4 * b + t + 1], xl[4 * b + t + 1]);
          mma1688(dh[0], xh[4 * b + t], xh[4 * b + t + 1], xh[4 * b + t]);
          mma1688(dh[1], xh[4 * b + t], xh[4 * b + t + 1], xh[4 * b + t + 1]);
        }
      }
      const float mlo = (sl[0] + sl[2]) * (1.f / D_), mhi = (sh[0] + sh[2]) * (1.f / D_);
      float ql = (rq & 1) ? dl[0][1] + dl[1][3] : dl[0][0] + dl[1][2];
      float qh = (rq & 1) ? dh[0][1] + dh[1][3] : dh[0][0] + dh[1][2];
      ql = __shfl_sync(0xffffffffu, ql, (lane & 28) | (rq >> 1));
      qh = __shfl_sync(0xffffffffu, qh, (lane & 28) | (rq >> 1));
      rlo = rsqrtf(fmaxf(ql * (1.f / D_) - mlo * mlo, 0.f) + 1e-5f);
      rhi = rsqrtf(fmaxf(qh * (1.f / D_) - mhi * mhi, 0.f) + 1e-5f);
      const uint32_t ml = pack2(mlo, mlo), mh = pack2(mhi, mhi);
#pragma unroll
      for (int s = 0; s < 36; s++) {
        a[4 * s] = hsub2(xl[2 * s], ml); a[4 * s + 1] = hsub2(xh[2 * s], mh);
        a[4 * s + 2] = hsub2(xl[2 * s + 1], ml); a[4 * s + 3] = hsub2(xh[2 * s + 1], mh);
      }
    }
    TS(1);
    bar_sync(BAR_INIT, 384);
    const uint32_t o40 = odd;
    const int c40 = odd ? 0 : 32, c32 = odd ? 40 : 0;
    uint32_t fq[36];
    {
      float k40[20], k32[16], v40[20], v32[16], p[36];
      stage_c<12, 0, 64, 0>(k32, a, 0);
      stage_c<12, 12, 64, 1>(k32, a, 0);    wg_wait<1>(); release(sb, 0, lane);
      stage_c<12, 24, 64, 2>(k32, a, 0);    wg_wait<1>(); release(sb, 1, lane);
      stage_c<6, 0, 128, 3>(k40, a, o40);   wg_wait<1>(); pin(k32); release(sb, 2, lane);
      stage_c<6, 6, 128, 4>(k40, a, o40);
      bar_sync(BAR_PREP, 352);
      phi_mma0(p, k32, rlo, rhi, sb);             wg_wait<1>(); release(sb, 3, lane); release(sb, 4, lane);
      stage_c<6, 12, 128, 5>(k40, a, o40);
      stage_c<6, 18, 128, 6>(k40, a, o40);  wg_wait<1>(); release(sb, 5, lane);
      stage_c<6, 24, 128, 7>(k40, a, o40);  wg_wait<1>(); release(sb, 6, lane);
      stage_c<6, 30, 128, 8>(k40, a, o40);  wg_wait<1>(); release(sb, 7, lane);
      wg_wait<0>(); pin(k40); release(sb, 8, lane);
      TS(2);
      phi_mma1(p, k40, rlo, rhi, sb);
      stage_c<6, 0, 128, 9>(v40, a, o40);   wg_wait<1>(); pin(p);
      const uint32_t prow = sb + OFF_PHI + c * 16384 + (warp * 16 + rq) * 128;
      stage_c<6, 6, 128, 10>(v40, a, o40);
      stage_c<6, 12, 128, 11>(v40, a, o40); phik_piece<0, 0>(p, prow, c, rq); wg_wait<1>(); release(sb, 9, lane); release(sb, 10, lane);
      stage_c<6, 18, 128, 12>(v40, a, o40); phik_piece<0, 1>(p, prow, c, rq); wg_wait<1>(); release(sb, 11, lane);
      stage_c<6, 24, 128, 13>(v40, a, o40); phik_piece<1, 0>(p, prow, c, rq); wg_wait<1>(); release(sb, 12, lane);
      stage_c<6, 30, 128, 14>(v40, a, o40); phik_piece<1, 1>(p, prow, c, rq); wg_wait<1>(); release(sb, 13, lane);
      stage_c<12, 0, 64, 15>(v32, a, 0);    wg_wait<1>(); release(sb, 14, lane);
      stage_c<12, 12, 64, 16>(v32, a, 0);   wg_wait<1>(); release(sb, 15, lane);
      stage_c<12, 24, 64, 17>(v32, a, 0);   wg_wait<1>(); release(sb, 16, lane);
      TS(3);
      stage_c<12, 0, 64, 18>(k32, a, 0);    wg_wait<1>(); pin(v40); pin(v32); release(sb, 17, lane);
      {
        const uint32_t vrow = sb + OFF_V + (warp * 16 + rq) * 16;
#pragma unroll
        for (int j = 0; j < 9; j++) {
          const int col = (j < 5 ? c40 + 8 * j : c32 + 8 * (j - 5)) + 2 * c;
          const int h = col / 18, d = col - 18 * h;
          const uint32_t ad = vrow + h * 6144 + (d >> 3) * 2048 + (d & 7) * 2;
          const float* v = j < 5 ? &v40[4 * j] : &v32[4 * (j - 5)];
          sts32(ad, pack2(v[0] * rlo, v[1] * rlo));
          sts32(ad + 128, pack2(v[2] * rhi, v[3] * rhi));
        }
      }
      fence_async_smem();
      bar_sync(BAR_KVIN, 256);
      float kv0[12], kv1[12];
      const int h0 = (warp >> 2) * 2;
      {
        wg_fence();
        const uint64_t da = make_desc(sb + OFF_PHI + h0 * 16384, 16, 1024, 1), db = make_desc(sb + OFF_V + h0 * 6144, 128, 2048, 0);
#pragma unroll
        for (int s = 0; s < 8; s++) {
          wgmma_ss_tt(kv0, da + (uint64_t)(s * 128), db + (uint64_t)(s * 16), s != 0);
          wgmma_ss_tt(kv1, da + (uint64_t)(s * 128 + 1024), db + (uint64_t)(s * 16 + 384), s != 0);
        }
        wg_commit();
      }
      stage_c<12, 12, 64, 19>(k32, a, 0);   wg_wait<1>(); pin(kv0); pin(kv1); release(sb, 18, lane);
      stage_c<12, 24, 64, 20>(k32, a, 0);
      bar_sync(7 + (warp >> 2), 128);
#pragma unroll
      for (int hh = 0; hh < 2; hh++) {
#pragma unroll
        for (int u = 0; u < 2; u++) {
          const int L = 2 * (warp & 3) + u;
          const int f = 8 * ((L - 2 * (h0 + hh)) & 7) + rq;
          if (f < 36) {
            const uint32_t ad = sb + OFF_V + (h0 + hh) * 6144 + f * 80 + c * 8;
            const float* kvp = hh ? kv1 : kv0;
            sts64(ad, __float_as_uint(kvp[2 * u]), __float_as_uint(kvp[2 * u + 1]));
            sts64(ad + 32, __float_as_uint(kvp[4 + 2 * u]), __float_as_uint(kvp[5 + 2 * u]));
            if (c < 2) sts64(ad + 64, __float_as_uint(kvp[8 + 2 * u]), __float_as_uint(kvp[9 + 2 * u]));
          }
        }
      }
      fence_async_smem();
      bar_arrive(BAR_KVOUT, 288);
      wg_wait<1>(); release(sb, 19, lane);
      stage_c<6, 0, 128, 21>(k40, a, o40);  wg_wait<1>(); pin(k32); release(sb, 20, lane);
      stage_c<6, 6, 128, 22>(k40, a, o40);
      phi_mma0(p, k32, rlo, rhi, sb);             wg_wait<1>(); release(sb, 21, lane); release(sb, 22, lane);
      stage_c<6, 12, 128, 23>(k40, a, o40);
      stage_c<6, 18, 128, 24>(k40, a, o40); wg_wait<1>(); release(sb, 23, lane);
      stage_c<6, 24, 128, 25>(k40, a, o40); wg_wait<1>(); release(sb, 24, lane);
      stage_c<6, 30, 128, 26>(k40, a, o40); wg_wait<1>(); release(sb, 25, lane);
      wg_wait<0>(); pin(k40); release(sb, 26, lane);
      TS(4);
      phi_mma1(p, k40, rlo, rhi, sb);
      wg_wait<0>(); pin(p);
      phiq_piece<0, 0>(p, fq); phiq_piece<1, 0>(p, fq); phiq_piece<0, 1>(p, fq); phiq_piece<1, 1>(p, fq);
    }
    TS(5);
    uint32_t xr[18], b2r[9];
#pragma unroll
    for (int j = 0; j < 9; j++) {
      const int col = 72 * g + 8 * j + 2 * c;
      xr[2 * j] = ldg32_nc(P.x + (size_t)row * D_ + col);
      xr[2 * j + 1] = ldg32_nc(P.x + (size_t)(row + 8) * D_ + col);
      b2r[j] = ldg32_nc(P.b2 + col);
    }
    const int rw = r * 8 + warp;
    {
      float o[44];
      bar_sync(BAR_KVB, 352);
      TS(6);
      wg_fence();
      static_for<0, 9>([&](auto s) { wgmma_rs<desc_lo(SB + OFF_KVB + s.value * 256, 128), desc_hi(2304, 0), s.value != 0>(o, fq[4 * s.value], fq[4 * s.value + 1], fq[4 * s.value + 2], fq[4 * s.value + 3], 0); });
      wg_commit();
      wg_wait<0>(); pin(o);
      uint32_t f[18];
#pragma unroll
      for (int u = 0; u < 2; u++) {
        const float i0 = rcp(o[36 + 2 * u] + 1e-6f), i1 = rcp(o[37 + 2 * u] + 1e-6f), i2 = rcp(o[40 + 2 * u] + 1e-6f), i3 = rcp(o[41 + 2 * u] + 1e-6f);
        const float sc[9] = {i0, i0, c < 1 ? i0 : i1, i1, c < 2 ? i1 : i2, i2, c < 3 ? i2 : i3, i3, i3};
#pragma unroll
        for (int j = 0; j < 9; j++) f[2 * j + u] = pack2(o[4 * j + 2 * u] * sc[j], o[4 * j + 2 * u + 1] * sc[j]);
      }
      store_frag(g_o + rw * 36 * 32 + lane, f, g);
      __syncwarp();
      if (lane == 0) { signal(&g_cnt_o[rw * 32]); TS(7); poll(&g_cnt_o[rw * 32], (ep + 1) * 8); }
      __syncwarp();
    }
    TS(8);
    {
      const uint4* op = g_o + rw * 36 * 32 + lane;
#pragma unroll
      for (int s = 0; s < 36; s++) ldg128_cg(op + s * 32, a[4 * s], a[4 * s + 1], a[4 * s + 2], a[4 * s + 3]);
      float h40[20], h32[16];
      stage_c<6, 0, 128, 27>(h40, a, o40);
      stage_c<6, 6, 128, 28>(h40, a, o40);  wg_wait<1>(); release(sb, 27, lane);
      stage_c<12, 0, 64, 29>(h32, a, 0);    wg_wait<1>(); release(sb, 28, lane);
      stage_c<6, 12, 128, 30>(h40, a, o40); wg_wait<1>(); release(sb, 29, lane);
      stage_c<6, 18, 128, 31>(h40, a, o40); wg_wait<1>(); release(sb, 30, lane);
      stage_c<12, 12, 64, 32>(h32, a, 0);   wg_wait<1>(); release(sb, 31, lane);
      stage_c<6, 24, 128, 33>(h40, a, o40); wg_wait<1>(); release(sb, 32, lane);
      stage_c<6, 30, 128, 34>(h40, a, o40); wg_wait<1>(); release(sb, 33, lane);
      stage_c<12, 24, 64, 35>(h32, a, 0);   wg_wait<1>(); release(sb, 34, lane);
      wg_wait<0>(); pin(h40); pin(h32); release(sb, 35, lane);
      TS(9);
      uint32_t f[18];
      float sl = 0.f, ql = 0.f, sh = 0.f, qh = 0.f;
#pragma unroll
      for (int j = 0; j < 9; j++) {
        float v[4];
#pragma unroll
        for (int e = 0; e < 4; e++) {
          const float ve = (j < 4) ? h32[4 * j + e] : h40[4 * (j - 4)  + e];
          const float vo = (j < 5) ? h40[4 * j + e] : h32[4 * (j - 5) + e];
          v[e] = odd ? vo : ve;
        }
        f[2 * j] = pack2(v[0] + bf_lo(xr[2 * j]), v[1] + bf_hi(xr[2 * j]));
        f[2 * j + 1] = pack2(v[2] + bf_lo(xr[2 * j + 1]), v[3] + bf_hi(xr[2 * j + 1]));
      }
      store_frag(g_h + rw * 36 * 32 + lane, f, g);
#pragma unroll
      for (int j = 0; j < 9; j++) {
        const float l0 = bf_lo(f[2 * j]), l1 = bf_hi(f[2 * j]), u0 = bf_lo(f[2 * j + 1]), u1 = bf_hi(f[2 * j + 1]);
        sl += l0 + l1; ql = fmaf(l0, l0, fmaf(l1, l1, ql));
        sh += u0 + u1; qh = fmaf(u0, u0, fmaf(u1, u1, qh));
        const int col = 72 * g + 8 * j + 2 * c;
        stg32(P.out + (size_t)row * D_ + col, pack2(l0 + bf_lo(b2r[j]), l1 + bf_hi(b2r[j])));
        stg32(P.out + (size_t)(row + 8) * D_ + col, pack2(u0 + bf_lo(b2r[j]), u1 + bf_hi(b2r[j])));
      }
#pragma unroll
      for (int m = 1; m < 4; m <<= 1) {
        sl += __shfl_xor_sync(0xffffffffu, sl, m); ql += __shfl_xor_sync(0xffffffffu, ql, m);
        sh += __shfl_xor_sync(0xffffffffu, sh, m); qh += __shfl_xor_sync(0xffffffffu, qh, m);
      }
      if (c < 2) stg64(&g_stats[(row + 8 * c) * 8 + g], __float_as_uint(c ? sh : sl), __float_as_uint(c ? qh : ql));
      __syncwarp();
      if (lane == 0) { signal(&g_cnt_h[rw * 32]); TS(10); poll(&g_cnt_h[rw * 32], (ep + 1) * 8); asm volatile("fence.proxy.async.global;" ::: "memory"); }
      __syncwarp();
    }
    TS(11);
    float accA[32], accB[32];
    {
      uint32_t s0, s1, s2, s3, t0, t1, t2, t3;
      ldg128_cg(&g_stats[row * 8 + 2 * c], s0, s1, s2, s3);
      ldg128_cg(&g_stats[(row + 8) * 8 + 2 * c], t0, t1, t2, t3);
      const uint4* hp = g_h + rw * 36 * 32 + lane;
#pragma unroll
      for (int s = 0; s < 36; s++) ldg128_cg(hp + s * 32, a[4 * s], a[4 * s + 1], a[4 * s + 2], a[4 * s + 3]);
      float sl = __uint_as_float(s0) + __uint_as_float(s2), ql = __uint_as_float(s1) + __uint_as_float(s3);
      float sh = __uint_as_float(t0) + __uint_as_float(t2), qh = __uint_as_float(t1) + __uint_as_float(t3);
#pragma unroll
      for (int m = 1; m < 4; m <<= 1) {
        sl += __shfl_xor_sync(0xffffffffu, sl, m); ql += __shfl_xor_sync(0xffffffffu, ql, m);
        sh += __shfl_xor_sync(0xffffffffu, sh, m); qh += __shfl_xor_sync(0xffffffffu, qh, m);
      }
      sl *= (1.f / D_); sh *= (1.f / D_);
      rlo = rsqrtf(fmaxf(ql * (1.f / D_) - sl * sl, 0.f) + 1e-5f);
      rhi = rsqrtf(fmaxf(qh * (1.f / D_) - sh * sh, 0.f) + 1e-5f);
      const uint32_t ml = pack2(sl, sl), mh = pack2(sh, sh);
      auto center = [&](int k0) {
#pragma unroll
        for (int i = 4 * k0; i < 4 * k0 + 24; i++) a[i] = hsub2(a[i], (i & 1) ? mh : ml);
      };
      center(0);  stage_c<6, 0, 128, 36>(accA, a, 0);
      center(6);  stage_c<6, 6, 128, 37>(accA, a, 0);  wg_wait<1>(); release(sb, 36, lane);
      center(12); stage_c<6, 12, 128, 38>(accA, a, 0); wg_wait<1>(); release(sb, 37, lane);
      center(18); stage_c<6, 18, 128, 39>(accA, a, 0); wg_wait<1>(); release(sb, 38, lane);
      center(24); stage_c<6, 24, 128, 40>(accA, a, 0); wg_wait<1>(); release(sb, 39, lane);
      center(30);
    }
    TS(12);
    const uint32_t xw = sb + OFF_X + warp * 16384;
    uint32_t it = 41;
    {
      uint32_t b1a = sb + OFF_B1 + c * 16, hd = xw + lane * 16;
#pragma unroll 1
      for (int pp = 0; pp < 4; pp++) {
        ffn_tail(accA, a, sb, it, lane);
        ffn_head(accB, accA, a, sb, it + 1, lane, [&](auto q) { gelu_sts<q.value>(accA, rlo, rhi, b1a, hd); });
        ffn_tail(accB, a, sb, it + 6, lane);
        ffn_head(accA, accB, a, sb, it + 7, lane, [&](auto q) { gelu_sts<q.value>(accB, rlo, rhi, b1a + 256, hd + 2048); });
        it += 12; b1a += 512; hd += 4096;
      }
      ffn_tail(accA, a, sb, it, lane);
      TS(13);
      wg_wait<0>(); pin(accA);
#pragma unroll
      for (int s = 0; s < 32; s++) lds128(xw + lane * 16 + s * 512, a[4 * s], a[4 * s + 1], a[4 * s + 2], a[4 * s + 3]);
      __syncwarp();
      ffn_head(accB, accA, a, sb, it + 1, lane, [&](auto q) {
        gelu_chunk<q.value>(accA, rlo, rhi, b1a, a[128 + 4 * q.value], a[129 + 4 * q.value], a[130 + 4 * q.value], a[131 + 4 * q.value]);
      });
      it += 6;
    }
    TS(14);
    {
      const int orow = (lane & 7) + (lane & 8);
      const int x7 = (lane & 7) ^ (lane >> 4);
      const int grow = r * 128 + warp * 16;
      uint32_t st = xw;
      int col = 0;
#pragma unroll 1
      for (int pp = 0; pp < 4; pp++) {
        ffn_tail(accB, a, sb, it, lane);
        ffn_head(accA, accB, a, sb, it + 1, lane, [&](auto q) {
          out_chunk<q.value>(accB, st + orow * 128, x7); if constexpr (q.value == 3) out_send(&P.tout, st, col, grow, lane); });
        ffn_tail(accA, a, sb, it + 6, lane);
        ffn_head(accB, accA, a, sb, it + 7, lane, [&](auto q) {
          out_chunk<q.value>(accA, st + 2048 + orow * 128, x7); if constexpr (q.value == 3) out_send(&P.tout, st + 2048, col + 64, grow, lane); });
        it += 12; st += 4096; col += 128;
      }
      ffn_tail(accB, a, sb, it, lane);
      if (lane == 0) asm volatile("cp.async.bulk.wait_group.read 7;" ::: "memory");
      __syncwarp();
      wg_wait<0>(); pin(accB);
      TS(15);
      out_chunk<0>(accB, xw + orow * 128, x7); out_chunk<1>(accB, xw + orow * 128, x7);
      out_chunk<2>(accB, xw + orow * 128, x7); out_chunk<3>(accB, xw + orow * 128, x7);
      out_send(&P.tout, xw, 512, grow, lane);
      if (lane == 0) asm volatile("cp.async.bulk.wait_group 0;" ::: "memory");
      if (tid == 0) g_epoch[blk] = ep + 1;
      TS(16);
      TS_DUMP();
    }
  }
}

typedef CUresult (*EncodeFn)(CUtensorMap*, CUtensorMapDataType, cuuint32_t, void*, const cuuint64_t*, const cuuint64_t*, const cuuint32_t*,
                             const cuuint32_t*, CUtensorMapInterleave, CUtensorMapSwizzle, CUtensorMapL2promotion, CUtensorMapFloatOOBfill);

void enc2d(EncodeFn fn, CUtensorMap* m, const void* base, uint64_t cols, uint64_t rows, uint32_t bc, uint32_t br) {
  cuuint64_t gd[2] = {cols, rows}, gs[1] = {cols * 2};
  cuuint32_t bd[2] = {bc, br}, es[2] = {1, 1};
  fn(m, CU_TENSOR_MAP_DATA_TYPE_BFLOAT16, 2, const_cast<void*>(base), gd, gs, bd, es, CU_TENSOR_MAP_INTERLEAVE_NONE,
     bc == 64 ? CU_TENSOR_MAP_SWIZZLE_128B : CU_TENSOR_MAP_SWIZZLE_64B, CU_TENSOR_MAP_L2_PROMOTION_L2_128B, CU_TENSOR_MAP_FLOAT_OOB_FILL_NONE);
}
void enc5d(EncodeFn fn, CUtensorMap* m, const void* base, uint64_t cols, uint32_t bc, uint32_t nb) {
  cuuint64_t gd[5] = {cols, 2, 4, 4, 18}, gs[4] = {cols * 2, cols * 16, cols * 4, cols * 64};
  cuuint32_t bd[5] = {bc, 2, 4, 4, nb}, es[5] = {1, 1, 1, 1, 1};
  fn(m, CU_TENSOR_MAP_DATA_TYPE_BFLOAT16, 5, const_cast<void*>(base), gd, gs, bd, es, CU_TENSOR_MAP_INTERLEAVE_NONE,
     bc == 64 ? CU_TENSOR_MAP_SWIZZLE_128B : CU_TENSOR_MAP_SWIZZLE_64B, CU_TENSOR_MAP_L2_PROMOTION_L2_128B, CU_TENSOR_MAP_FLOAT_OOB_FILL_NONE);
}

}

extern "C" void kernel_launch(void* const* d_in, const int* in_sizes, int n_in, void* d_out, int out_size) {
  (void)in_sizes; (void)n_in; (void)out_size;
  static EncodeFn fn = nullptr;
  if (!fn) {
    void* p = nullptr;
    cudaDriverEntryPointQueryResult q;
    cudaGetDriverEntryPoint("cuTensorMapEncodeTiled", &p, cudaEnableDefault, &q);
    fn = (EncodeFn)p;
    cudaFuncSetAttribute(fused_block_kernel, cudaFuncAttributeMaxDynamicSharedMemorySize, SMEM_BYTES);
  }
  Params P;
  P.x = (const __nv_bfloat16*)d_in[0];
  P.wqkv = (const __nv_bfloat16*)d_in[1];
  P.wphi = (const __nv_bfloat16*)d_in[2];
  P.wo = (const __nv_bfloat16*)d_in[3];
  P.w1 = (const __nv_bfloat16*)d_in[5];
  P.b1 = (const __nv_bfloat16*)d_in[6];
  P.w2 = (const __nv_bfloat16*)d_in[7];
  P.b2 = (const __nv_bfloat16*)d_in[8];
  P.out = (__nv_bfloat16*)d_out;
  enc5d(fn, &P.tq64, P.wqkv, 3 * D_, 64, 3);
  enc5d(fn, &P.tq32, P.wqkv, 3 * D_, 32, 6);
  enc2d(fn, &P.to64, P.wo, D_, D_, 64, 96);
  enc2d(fn, &P.to32, P.wo, D_, D_, 32, 192);
  enc2d(fn, &P.tw1, P.w1, F_, D_, 64, 96);
  enc2d(fn, &P.tw2, P.w2, D_, F_, 64, 96);
  enc2d(fn, &P.tout, P.out, D_, S_, 64, 16);
  fused_block_kernel<<<128, 384, SMEM_BYTES>>>(P);
}
```

```cpp
#include <cuda_runtime.h>
#include <cuda.h>
#include <cuda_bf16.h>
#include <stdint.h>
#include <type_traits>

namespace {

constexpr int S_ = 2048, D_ = 576, F_ = 4608;
constexpr int NSLOT = 8, SLOT_BYTES = 12288;
constexpr uint32_t SB       = 1024;
constexpr uint32_t A_X      = SB + NSLOT * SLOT_BYTES;
constexpr uint32_t A_XT     = A_X - 16384;
constexpr uint32_t A_PHI    = A_X;
constexpr uint32_t A_V      = A_X + 65536;
constexpr uint32_t A_WPHI   = A_X + 90112;
constexpr uint32_t A_KVB    = A_X + 101632;
constexpr uint32_t A_B1     = A_X + 131072;
constexpr uint32_t A_FULL   = A_B1 + 2304;
constexpr uint32_t A_EMPTY  = A_FULL + 64;
constexpr uint32_t A_LAND   = A_FULL + 128;
constexpr uint32_t A_XFREE  = A_LAND + 80;
constexpr uint32_t A_KVL    = A_XFREE + 8;
constexpr uint32_t A_OUTRDY = A_KVL + 8;
constexpr uint32_t A_TS     = A_OUTRDY + 8;
constexpr uint32_t SMEM_BYTES = A_TS + 256 - SB;
static_assert((A_FULL & 63) == 0, "barrier block alignment");
constexpr int SPIN_LIMIT = 1 << 20;

enum { BAR_INIT = 1, BAR_PREP = 2, BAR_KVIN = 3, BAR_KVOUT = 4, BAR_KVB = 5, BAR_HELP = 6, BAR_WG = 7  , BAR_OMMA = 9 };

struct Params {
  CUtensorMap tx, tq64, tq32, to64, to32, tw1, tw2, tout, tgo, tgh;
  const __nv_bfloat16 *x, *wqkv, *wphi, *wo, *w1, *b1, *w2, *b2;
  __nv_bfloat16* out;
  uint64_t d128, d64, dwphi, dkvb, dphi, dv;
};

__device__ uint4    g_o[128 * 36 * 32];
__device__ uint4    g_h[128 * 36 * 32];
__device__ float4   g_stats[128 * 64];
__device__ float4   g_kv[2 * 8 * 720];
__device__ unsigned g_cnt[(8 + 32 + 32 + 16) * 32];
__device__ unsigned g_epoch[128];
#define TSX(t, i)
#define TS(i)
#define TS_DUMP()

__device__ __forceinline__ void mbar_init(uint32_t bar, uint32_t cnt) { asm volatile("mbarrier.init.shared::cta.b64 [%0], %1;" ::"r"(bar), "r"(cnt)); }
__device__ __forceinline__ void mbar_expect_tx(uint32_t bar, uint32_t bytes) { asm volatile("mbarrier.arrive.expect_tx.shared::cta.b64 _, [%0], %1;" ::"r"(bar), "r"(bytes) : "memory"); }
__device__ __forceinline__ void mbar_arrive(uint32_t bar) { asm volatile("mbarrier.arrive.shared::cta.b64 _, [%0];" ::"r"(bar) : "memory"); }
__device__ __forceinline__ void mbar_wait(uint32_t bar, uint32_t parity) {
  asm volatile(
      "{\n.reg .pred p;\n"
      "WAIT_%=:\n"
      "mbarrier.try_wait.parity.shared::cta.b64 p, [%0], %1;\n"
      "@p bra DONE_%=;\n"
      "bra WAIT_%=;\n"
      "DONE_%=:\n}\n" ::"r"(bar), "r"(parity) : "memory");
}
template <int ID, int N> __device__ __forceinline__ void bar_sync() { asm volatile("bar.sync %0, %1;" ::"n"(ID), "n"(N) : "memory"); }
template <int ID, int N> __device__ __forceinline__ void bar_arrive() { asm volatile("bar.arrive %0, %1;" ::"n"(ID), "n"(N) : "memory"); }
__device__ __forceinline__ void bar_sync_wg(int wg) { asm volatile("bar.sync %0, 128;" ::"r"(BAR_WG + wg) : "memory"); }
__device__ __forceinline__ void fence_async_smem() { asm volatile("fence.proxy.async.shared::cta;" ::: "memory"); }
__device__ __forceinline__ void fence_async_global() { asm volatile("fence.proxy.async.global;" ::: "memory"); }
__device__ __forceinline__ void tma2d(uint32_t dst, const CUtensorMap* m, int c0, int c1, uint32_t bar) {
  asm volatile("cp.async.bulk.tensor.2d.shared::cluster.global.mbarrier::complete_tx::bytes [%0], [%1, {%3, %4}], [%2];" ::"r"(dst), "l"(m), "r"(bar), "r"(c0), "r"(c1) : "memory");
}
__device__ __forceinline__ void tma3d(uint32_t dst, const CUtensorMap* m, int c1, int c2, uint32_t bar) {
  asm volatile("cp.async.bulk.tensor.3d.shared::cluster.global.mbarrier::complete_tx::bytes [%0], [%1, {%5, %3, %4}], [%2];" ::"r"(dst), "l"(m), "r"(bar), "r"(c1), "r"(c2), "r"(0) : "memory");
}
__device__ __forceinline__ void bulk_load(uint32_t dst, const void* src, uint32_t bytes, uint32_t bar) {
  asm volatile("cp.async.bulk.shared::cluster.global.mbarrier::complete_tx::bytes [%0], [%1], %2, [%3];" ::"r"(dst), "l"(src), "r"(bytes), "r"(bar) : "memory");
}
__device__ __forceinline__ void bulk_store(void* dst, uint32_t src, uint32_t bytes) {
  asm volatile("cp.async.bulk.global.shared::cta.bulk_group [%0], [%1], %2;" ::"l"(dst), "r"(src), "r"(bytes) : "memory");
}
__device__ __forceinline__ void bulk_commit() { asm volatile("cp.async.bulk.commit_group;" ::: "memory"); }
__device__ __forceinline__ void bulk_wait_all() { asm volatile("cp.async.bulk.wait_group 0;" ::: "memory"); }
__device__ __forceinline__ void l2_prefetch(const void* p, uint32_t bytes) { asm volatile("cp.async.bulk.prefetch.L2.global [%0], %1;" ::"l"(p), "r"(bytes) : "memory"); }
__device__ __forceinline__ void wg_fence() { asm volatile("wgmma.fence.sync.aligned;" ::: "memory"); }
__device__ __forceinline__ void wg_commit() { asm volatile("wgmma.commit_group.sync.aligned;" ::: "memory"); }
template <int N> __device__ __forceinline__ void wg_wait() { asm volatile("wgmma.wait_group.sync.aligned %0;" ::"n"(N) : "memory"); }
template <int N> __device__ __forceinline__ void pin(float (&d)[N]) {
#pragma unroll
  for (int i = 0; i < N; i++) asm volatile("" : "+f"(d[i])::"memory");
}
__device__ __forceinline__ uint32_t pack2(float lo, float hi) { uint32_t r; asm("cvt.rn.bf16x2.f32 %0, %1, %2;" : "=r"(r) : "f"(hi), "f"(lo)); return r; }
__device__ __forceinline__ float bf_lo(uint32_t v) { return __uint_as_float(v << 16); }
__device__ __forceinline__ float bf_hi(uint32_t v) { return __uint_as_float(v & 0xffff0000u); }
__device__ __forceinline__ uint32_t hsub2(uint32_t a, uint32_t b) { uint32_t r; asm("sub.rn.bf16x2 %0, %1, %2;" : "=r"(r) : "r"(a), "r"(b)); return r; }
__device__ __forceinline__ uint32_t hadd2(uint32_t a, uint32_t b) { uint32_t r; asm("add.rn.bf16x2 %0, %1, %2;" : "=r"(r) : "r"(a), "r"(b)); return r; }
__device__ __forceinline__ float ex2(float x) { float r; asm("ex2.approx.ftz.f32 %0, %1;" : "=f"(r) : "f"(x)); return r; }
__device__ __forceinline__ float rcp(float x) { float r; asm("rcp.approx.ftz.f32 %0, %1;" : "=f"(r) : "f"(x)); return r; }
__device__ __forceinline__ float rsq(float x) { float r; asm("rsqrt.approx.ftz.f32 %0, %1;" : "=f"(r) : "f"(x)); return r; }
__device__ __forceinline__ float tanh_(float x) { float r; asm("tanh.approx.f32 %0, %1;" : "=f"(r) : "f"(x)); return r; }
__device__ __forceinline__ void mma16816(float (&d)[4], uint32_t a0, uint32_t a1, uint32_t a2, uint32_t a3, uint32_t b0, uint32_t b1) {
  asm("mma.sync.aligned.m16n8k16.row.col.f32.bf16.bf16.f32 {%0,%1,%2,%3}, {%4,%5,%6,%7}, {%8,%9}, {%0,%1,%2,%3};"
      : "+f"(d[0]), "+f"(d[1]), "+f"(d[2]), "+f"(d[3]) : "r"(a0), "r"(a1), "r"(a2), "r"(a3), "r"(b0), "r"(b1));
}
__device__ __forceinline__ void mma1688(float (&d)[4], uint32_t a0, uint32_t a1, uint32_t b0) {
  asm("mma.sync.aligned.m16n8k8.row.col.f32.bf16.bf16.f32 {%0,%1,%2,%3}, {%4,%5}, {%6}, {%0,%1,%2,%3};"
      : "+f"(d[0]), "+f"(d[1]), "+f"(d[2]), "+f"(d[3]) : "r"(a0), "r"(a1), "r"(b0));
}
__device__ __forceinline__ void sts32(uint32_t a, uint32_t v) { asm volatile("st.shared.b32 [%0], %1;" ::"r"(a), "r"(v) : "memory"); }
__device__ __forceinline__ void sts64(uint32_t a, uint32_t v0, uint32_t v1) { asm volatile("st.shared.v2.b32 [%0], {%1,%2};" ::"r"(a), "r"(v0), "r"(v1) : "memory"); }
__device__ __forceinline__ void sts128(uint32_t a, uint32_t v0, uint32_t v1, uint32_t v2, uint32_t v3) { asm volatile("st.shared.v4.b32 [%0], {%1,%2,%3,%4};" ::"r"(a), "r"(v0), "r"(v1), "r"(v2), "r"(v3) : "memory"); }
__device__ __forceinline__ void lds64(uint32_t a, uint32_t& v0, uint32_t& v1) { asm volatile("ld.shared.v2.b32 {%0,%1}, [%2];" : "=r"(v0), "=r"(v1) : "r"(a) : "memory"); }
__device__ __forceinline__ void lds128(uint32_t a, uint32_t& v0, uint32_t& v1, uint32_t& v2, uint32_t& v3) { asm volatile("ld.shared.v4.b32 {%0,%1,%2,%3}, [%4];" : "=r"(v0), "=r"(v1), "=r"(v2), "=r"(v3) : "r"(a) : "memory"); }
__device__ __forceinline__ void ldsm4(uint32_t a, uint32_t& v0, uint32_t& v1, uint32_t& v2, uint32_t& v3) { asm volatile("ldmatrix.sync.aligned.m8n8.x4.shared.b16 {%0,%1,%2,%3}, [%4];" : "=r"(v0), "=r"(v1), "=r"(v2), "=r"(v3) : "r"(a) : "memory"); }
__device__ __forceinline__ void ldg128(const void* p, uint32_t& v0, uint32_t& v1, uint32_t& v2, uint32_t& v3) { asm volatile("ld.global.cg.v4.b32 {%0,%1,%2,%3}, [%4];" : "=r"(v0), "=r"(v1), "=r"(v2), "=r"(v3) : "l"(p) : "memory"); }
__device__ __forceinline__ void ldg64(const void* p, uint32_t& v0, uint32_t& v1) { asm volatile("ld.global.cg.v2.b32 {%0,%1}, [%2];" : "=r"(v0), "=r"(v1) : "l"(p) : "memory"); }
__device__ __forceinline__ uint32_t ldg32(const void* p) { uint32_t v; asm volatile("ld.global.b32 %0, [%1];" : "=r"(v) : "l"(p) : "memory"); return v; }
__device__ __forceinline__ void stg32(void* p, uint32_t v) { asm volatile("st.global.b32 [%0], %1;" ::"l"(p), "r"(v) : "memory"); }
__device__ __forceinline__ void signal(unsigned* c) { asm volatile("red.relaxed.gpu.global.add.u32 [%0], 1;" ::"l"(c) : "memory"); }
__device__ __forceinline__ void signal_release(unsigned* c) { asm volatile("red.release.gpu.global.add.u32 [%0], 1;" ::"l"(c) : "memory"); }
__device__ __forceinline__ void poll(const unsigned* c, unsigned target) {
  unsigned v; int n = 0;
  do { asm volatile("ld.relaxed.gpu.global.u32 %0, [%1];" : "=r"(v) : "l"(c) : "memory"); } while ((int)(v - target) < 0 && ++n < SPIN_LIMIT);
}

template <int INC, int SCALE_D>
__device__ __forceinline__ void wgmma_rs(float (&d)[16], uint32_t a0, uint32_t a1, uint32_t a2, uint32_t a3, uint64_t& bd) {
  asm volatile("{\n.reg .pred p;\nsetp.ne.b32 p, %22, 0;\n"
    "wgmma.mma_async.sync.aligned.m64n32k16.f32.bf16.bf16 {%0, %1, %2, %3, %4, %5, %6, %7, %8, %9, %10, %11, %12, %13, %14, %15}, {%17, %18, %19, %20}, %16, p, 1, 1, 1;\n"
    "add.s64 %16, %16, %21;\n}\n"
    : "+f"(d[0]), "+f"(d[1]), "+f"(d[2]), "+f"(d[3]), "+f"(d[4]), "+f"(d[5]), "+f"(d[6]), "+f"(d[7]), "+f"(d[8]), "+f"(d[9]), "+f"(d[10]), "+f"(d[11]), "+f"(d[12]), "+f"(d[13]), "+f"(d[14]), "+f"(d[15]), "+l"(bd)
    : "r"(a0), "r"(a1), "r"(a2), "r"(a3), "n"(INC), "n"(SCALE_D));
}
template <int INC, int SCALE_D>
__device__ __forceinline__ void wgmma_rs(float (&d)[20], uint32_t a0, uint32_t a1, uint32_t a2, uint32_t a3, uint64_t& bd) {
  asm volatile("{\n.reg .pred p;\nsetp.ne.b32 p, %26, 0;\n"
    "wgmma.mma_async.sync.aligned.m64n40k16.f32.bf16.bf16 {%0, %1, %2, %3, %4, %5, %6, %7, %8, %9, %10, %11, %12, %13, %14, %15, %16, %17, %18, %19}, {%21, %22, %23, %24}, %20, p, 1, 1, 1;\n"
    "add.s64 %20, %20, %25;\n}\n"
    : "+f"(d[0]), "+f"(d[1]), "+f"(d[2]), "+f"(d[3]), "+f"(d[4]), "+f"(d[5]), "+f"(d[6]), "+f"(d[7]), "+f"(d[8]), "+f"(d[9]), "+f"(d[10]), "+f"(d[11]), "+f"(d[12]), "+f"(d[13]), "+f"(d[14]), "+f"(d[15]), "+f"(d[16]), "+f"(d[17]), "+f"(d[18]), "+f"(d[19]), "+l"(bd)
    : "r"(a0), "r"(a1), "r"(a2), "r"(a3), "n"(INC), "n"(SCALE_D));
}
template <int INC, int SCALE_D>
__device__ __forceinline__ void wgmma_rs(float (&d)[32], uint32_t a0, uint32_t a1, uint32_t a2, uint32_t a3, uint64_t& bd) {
  asm volatile("{\n.reg .pred p;\nsetp.ne.b32 p, %38, 0;\n"
    "wgmma.mma_async.sync.aligned.m64n64k16.f32.bf16.bf16 {%0, %1, %2, %3, %4, %5, %6, %7, %8, %9, %10, %11, %12, %13, %14, %15, %16, %17, %18, %19, %20, %21, %22, %23, %24, %25, %26, %27, %28, %29, %30, %31}, {%33, %34, %35, %36}, %32, p, 1, 1, 1;\n"
    "add.s64 %32, %32, %37;\n}\n"
    : "+f"(d[0]), "+f"(d[1]), "+f"(d[2]), "+f"(d[3]), "+f"(d[4]), "+f"(d[5]), "+f"(d[6]), "+f"(d[7]), "+f"(d[8]), "+f"(d[9]), "+f"(d[10]), "+f"(d[11]), "+f"(d[12]), "+f"(d[13]), "+f"(d[14]), "+f"(d[15]), "+f"(d[16]), "+f"(d[17]), "+f"(d[18]), "+f"(d[19]), "+f"(d[20]), "+f"(d[21]), "+f"(d[22]), "+f"(d[23]), "+f"(d[24]), "+f"(d[25]), "+f"(d[26]), "+f"(d[27]), "+f"(d[28]), "+f"(d[29]), "+f"(d[30]), "+f"(d[31]), "+l"(bd)
    : "r"(a0), "r"(a1), "r"(a2), "r"(a3), "n"(INC), "n"(SCALE_D));
}
template <int INC, int SCALE_D>
__device__ __forceinline__ void wgmma_rs(float (&d)[36], uint32_t a0, uint32_t a1, uint32_t a2, uint32_t a3, uint64_t& bd) {
  asm volatile("{\n.reg .pred p;\nsetp.ne.b32 p, %42, 0;\n"
    "wgmma.mma_async.sync.aligned.m64n72k16.f32.bf16.bf16 {%0, %1, %2, %3, %4, %5, %6, %7, %8, %9, %10, %11, %12, %13, %14, %15, %16, %17, %18, %19, %20, %21, %22, %23, %24, %25, %26, %27, %28, %29, %30, %31, %32, %33, %34, %35}, {%37, %38, %39, %40}, %36, p, 1, 1, 1;\n"
    "add.s64 %36, %36, %41;\n}\n"
    : "+f"(d[0]), "+f"(d[1]), "+f"(d[2]), "+f"(d[3]), "+f"(d[4]), "+f"(d[5]), "+f"(d[6]), "+f"(d[7]), "+f"(d[8]), "+f"(d[9]), "+f"(d[10]), "+f"(d[11]), "+f"(d[12]), "+f"(d[13]), "+f"(d[14]), "+f"(d[15]), "+f"(d[16]), "+f"(d[17]), "+f"(d[18]), "+f"(d[19]), "+f"(d[20]), "+f"(d[21]), "+f"(d[22]), "+f"(d[23]), "+f"(d[24]), "+f"(d[25]), "+f"(d[26]), "+f"(d[27]), "+f"(d[28]), "+f"(d[29]), "+f"(d[30]), "+f"(d[31]), "+f"(d[32]), "+f"(d[33]), "+f"(d[34]), "+f"(d[35]), "+l"(bd)
    : "r"(a0), "r"(a1), "r"(a2), "r"(a3), "n"(INC), "n"(SCALE_D));
}
template <int INC, int SCALE_D>
__device__ __forceinline__ void wgmma_rs(float (&d)[44], uint32_t a0, uint32_t a1, uint32_t a2, uint32_t a3, uint64_t& bd) {
  asm volatile("{\n.reg .pred p;\nsetp.ne.b32 p, %50, 0;\n"
    "wgmma.mma_async.sync.aligned.m64n88k16.f32.bf16.bf16 {%0, %1, %2, %3, %4, %5, %6, %7, %8, %9, %10, %11, %12, %13, %14, %15, %16, %17, %18, %19, %20, %21, %22, %23, %24, %25, %26, %27, %28, %29, %30, %31, %32, %33, %34, %35, %36, %37, %38, %39, %40, %41, %42, %43}, {%45, %46, %47, %48}, %44, p, 1, 1, 1;\n"
    "add.s64 %44, %44, %49;\n}\n"
    : "+f"(d[0]), "+f"(d[1]), "+f"(d[2]), "+f"(d[3]), "+f"(d[4]), "+f"(d[5]), "+f"(d[6]), "+f"(d[7]), "+f"(d[8]), "+f"(d[9]), "+f"(d[10]), "+f"(d[11]), "+f"(d[12]), "+f"(d[13]), "+f"(d[14]), "+f"(d[15]), "+f"(d[16]), "+f"(d[17]), "+f"(d[18]), "+f"(d[19]), "+f"(d[20]), "+f"(d[21]), "+f"(d[22]), "+f"(d[23]), "+f"(d[24]), "+f"(d[25]), "+f"(d[26]), "+f"(d[27]), "+f"(d[28]), "+f"(d[29]), "+f"(d[30]), "+f"(d[31]), "+f"(d[32]), "+f"(d[33]), "+f"(d[34]), "+f"(d[35]), "+f"(d[36]), "+f"(d[37]), "+f"(d[38]), "+f"(d[39]), "+f"(d[40]), "+f"(d[41]), "+f"(d[42]), "+f"(d[43]), "+l"(bd)
    : "r"(a0), "r"(a1), "r"(a2), "r"(a3), "n"(INC), "n"(SCALE_D));
}
template <int INCA, int INCB, int SCALE_D>
__device__ __forceinline__ void wgmma_ss_tt(float (&d)[12], uint64_t& ad, uint64_t& bd) {
  asm volatile("{\n.reg .pred p;\nsetp.ne.b32 p, %16, 0;\n"
    "wgmma.mma_async.sync.aligned.m64n24k16.f32.bf16.bf16 {%0, %1, %2, %3, %4, %5, %6, %7, %8, %9, %10, %11}, %12, %13, p, 1, 1, 1, 1;\n"
    "add.s64 %12, %12, %14;\nadd.s64 %13, %13, %15;\n}\n"
    : "+f"(d[0]), "+f"(d[1]), "+f"(d[2]), "+f"(d[3]), "+f"(d[4]), "+f"(d[5]), "+f"(d[6]), "+f"(d[7]), "+f"(d[8]), "+f"(d[9]), "+f"(d[10]), "+f"(d[11]), "+l"(ad), "+l"(bd)
    : "n"(INCA), "n"(INCB), "n"(SCALE_D));
}

__host__ __device__ constexpr uint32_t desc_lo(uint32_t addr, uint32_t lbo) { return ((addr & 0x3FFFF) >> 4) | ((lbo >> 4) << 16); }
__host__ __device__ constexpr uint32_t desc_hi(uint32_t sbo, uint32_t swz) { return (sbo >> 4) | (swz << 30); }
__host__ __device__ constexpr uint64_t desc64(uint32_t addr, uint32_t lbo, uint32_t sbo, uint32_t swz) { return ((uint64_t)desc_hi(sbo, swz) << 32) | desc_lo(addr, lbo); }
template <uint32_t OFF> __device__ __forceinline__ uint64_t dadd(uint64_t base) {
  uint64_t d;
  asm volatile("add.s64 %0, %1, %2;" : "=l"(d) : "l"(base), "n"(OFF));
  return d;
}
template <int I, int N, class F> __device__ __forceinline__ void static_for(F f) {
  if constexpr (I < N) { f(std::integral_constant<int, I>{}); static_for<I + 1, N>(f); }
}

template <int KS, int K0, int ROWB, int NA>
__device__ __forceinline__ void stage_issue(float (&acc)[NA], const uint32_t (&a)[144], uint64_t d) {
  wg_fence();
  static_for<0, KS>([&](auto kk) {
    constexpr int k = K0 + kk.value;
    wgmma_rs<ROWB, k != 0>(acc, a[4 * k], a[4 * k + 1], a[4 * k + 2], a[4 * k + 3], d);
  });
  wg_commit();
}
template <int KS, int K0, int ROWB, int IT, int NA>
__device__ __forceinline__ void stage_c(float (&acc)[NA], const uint32_t (&a)[144], uint64_t base) {
  constexpr uint32_t slot = IT & (NSLOT - 1);
  mbar_wait(A_FULL + 8 * slot, (IT >> 3) & 1);
  stage_issue<KS, K0, ROWB>(acc, a, dadd<slot * (SLOT_BYTES / 16)>(base));
}
template <int IT> __device__ __forceinline__ void release_c(int lane) {
  if (lane == 0) mbar_arrive(A_EMPTY + 8 * (IT & (NSLOT - 1)));
}
template <int K0>
__device__ __forceinline__ void stage_r(float (&acc)[32], const uint32_t (&a)[144], uint32_t t8, uint64_t base) {
  const uint32_t s8 = t8 & 56;
  mbar_wait(A_FULL + s8, (t8 >> 6) & 1);
  stage_issue<6, K0, 128>(acc, a, base + s8 * (SLOT_BYTES / 128));
}
__device__ __forceinline__ void release_r(uint32_t t8, int lane) {
  if (lane == 0) mbar_arrive(A_EMPTY + (t8 & 56));
}

template <int HI, int NEG>
__device__ __forceinline__ void softmax18(const float (&p)[36], uint32_t (&w)[9]) {
  constexpr float L2E = NEG ? -1.4426950408889634f : 1.4426950408889634f;
  float m = p[2 * HI];
#pragma unroll
  for (int i = 1; i < 18; i++) { const float v = p[4 * (i >> 1) + 2 * HI + (i & 1)]; m = NEG ? fminf(m, v) : fmaxf(m, v); }
  m *= -L2E;
  float e[18], s = 0.f;
#pragma unroll
  for (int i = 0; i < 18; i++) { e[i] = ex2(fmaf(p[4 * (i >> 1) + 2 * HI + (i & 1)], L2E, m)); s += e[i]; }
  s = rcp(s);
#pragma unroll
  for (int t = 0; t < 9; t++) w[t] = pack2(e[2 * t] * s, e[2 * t + 1] * s);
}
template <int HI, int NEG>
__device__ __forceinline__ void phik_piece(const float (&p)[36], uint32_t rowaddr, int c, int t7) {
  uint32_t w[9];
  softmax18<HI, NEG>(p, w);
  rowaddr += HI * 1024;
  sts128(rowaddr + ((((2 * NEG + 2 * c) & 7) ^ t7) << 4), w[0], w[1], w[2], w[3]);
  sts128(rowaddr + ((((2 * NEG + 1 + 2 * c) & 7) ^ t7) << 4), w[4], w[5], w[6], w[7]);
  sts32(rowaddr + ((((4 + 2 * c) & 7) ^ t7) << 4) + 4 * NEG, w[8]);
}
template <int HI, int NEG>
__device__ __forceinline__ void phiq_piece(const float (&p)[36], uint32_t (&fq)[36]) {
  uint32_t w[9];
  softmax18<HI, NEG>(p, w);
#pragma unroll
  for (int t = 0; t < 8; t++) fq[2 * (8 * NEG + t) + HI] = w[t];
  fq[2 * (16 + NEG) + HI] = w[8];
}

__device__ __forceinline__ void phi_mma0(float (&p)[36], const float (&a32)[16], float rlo, float rhi, uint64_t d) {
  uint32_t f[8];
#pragma unroll
  for (int j = 0; j < 4; j++) { f[2 * j] = pack2(a32[4 * j] * rlo, a32[4 * j + 1] * rlo); f[2 * j + 1] = pack2(a32[4 * j + 2] * rhi, a32[4 * j + 3] * rhi); }
  wg_fence();
  static_for<0, 2>([&](auto s) { wgmma_rs<16, s.value != 0>(p, f[4 * s.value], f[4 * s.value + 1], f[4 * s.value + 2], f[4 * s.value + 3], d); });
  wg_commit();
}
__device__ __forceinline__ void phi_mma1(float (&p)[36], const float (&a40)[20], float rlo, float rhi, uint64_t d) {
  uint32_t f[12];
#pragma unroll
  for (int j = 0; j < 5; j++) { f[2 * j] = pack2(a40[4 * j] * rlo, a40[4 * j + 1] * rlo); f[2 * j + 1] = pack2(a40[4 * j + 2] * rhi, a40[4 * j + 3] * rhi); }
  f[10] = 0; f[11] = 0;
  d = dadd<32>(d);
  wg_fence();
  static_for<0, 3>([&](auto s) { wgmma_rs<16, 1>(p, f[4 * s.value], f[4 * s.value + 1], f[4 * s.value + 2], f[4 * s.value + 3], d); });
  wg_commit();
}

__device__ __forceinline__ void stage_piece(uint32_t st, int lane, int odd, const uint32_t (&f)[16], uint32_t s0, uint32_t s1) {
  const uint32_t pf = st + odd * 256 + lane * 16;
#pragma unroll
  for (int s = 0; s < 4; s++) sts128(pf + s * 512, f[4 * s], f[4 * s + 1], f[4 * s + 2], f[4 * s + 3]);
  sts64(st + (odd ? 0 : 2048) + lane * 8, s0, s1);
}
template <int C>
__device__ __forceinline__ void land_read(uint32_t (&a)[144], uint32_t base, int lane) {
  static_for<6 * C, 6 * C + 6>([&](auto s) {
    constexpr int k = s.value;
    constexpr uint32_t o = C * 12288 + (k - 6 * C) * 512;
    if constexpr (k % 9 == 4) { lds64(base + o + lane * 8, a[4 * k], a[4 * k + 1]); lds64(base + o + 256 + lane * 8, a[4 * k + 2], a[4 * k + 3]); }
    else lds128(base + o + lane * 16, a[4 * k], a[4 * k + 1], a[4 * k + 2], a[4 * k + 3]);
  });
}
__device__ __forceinline__ void tail_read(uint32_t (&a)[144], const uint4* blk, int lane) {
  static_for<30, 36>([&](auto s) {
    constexpr int k = s.value;
    if constexpr (k % 9 == 4) {
      const uint2* p = reinterpret_cast<const uint2*>(blk + k * 32) + lane;
      ldg64(p, a[4 * k], a[4 * k + 1]); ldg64(p + 32, a[4 * k + 2], a[4 * k + 3]);
    } else ldg128(blk + k * 32 + lane, a[4 * k], a[4 * k + 1], a[4 * k + 2], a[4 * k + 3]);
  });
}

__device__ __forceinline__ float gelu(float hy) {
  const float t = tanh_(hy * fmaf(hy * hy, 0.285419265090f, 1.595769121606f));
  return fmaf(hy, t, hy);
}
template <int K0, int Q>
__device__ __forceinline__ void stage_g(float (&acc)[32], const uint32_t (&a)[144], uint32_t t8, uint64_t base, bool on,
                                        const float (&y)[32], float rlo, float rhi, uint32_t b1addr, uint32_t dst) {
  const uint32_t s8 = t8 & 56;
  uint32_t b[4], o[4];
  if (on) lds128(b1addr + Q * 64, b[0], b[1], b[2], b[3]);
  mbar_wait(A_FULL + s8, (t8 >> 6) & 1);
  uint64_t d = base + s8 * (SLOT_BYTES / 128);
  wg_fence();
  static_for<0, 6>([&](auto kk) {
    constexpr int k = K0 + kk.value, e = kk.value - 1;
    wgmma_rs<128, 1>(acc, a[4 * k], a[4 * k + 1], a[4 * k + 2], a[4 * k + 3], d);
    if constexpr (e >= 0 && e < 4) {
      if (on) {
        const float rr = (e & 1) ? rhi : rlo;
        o[e] = pack2(gelu(fmaf(y[8 * Q + 2 * e], rr, __uint_as_float(b[e & 2]))), gelu(fmaf(y[8 * Q + 2 * e + 1], rr, __uint_as_float(b[(e & 2) + 1]))));
        if constexpr (e == 3) sts128(dst + Q * 512, o[0], o[1], o[2], o[3]); else asm volatile("" : "+r"(o[e]));
      }
    }
  });
  wg_commit();
}
__device__ __forceinline__ void out_tile(const float (&acc)[32], const CUtensorMap* m, uint32_t st, int col, int row, int lane) {
  const uint32_t ra = st + ((lane & 7) + (lane & 8)) * 128;
  const int x7 = (lane & 7) ^ (lane >> 4);
#pragma unroll
  for (int q = 0; q < 4; q++)
    asm volatile("stmatrix.sync.aligned.m8n8.x4.shared.b16 [%0], {%1,%2,%3,%4};" ::"r"(ra + (((2 * q) ^ x7) << 4)),
                 "r"(pack2(acc[8 * q + 0], acc[8 * q + 1])), "r"(pack2(acc[8 * q + 2], acc[8 * q + 3])),
                 "r"(pack2(acc[8 * q + 4], acc[8 * q + 5])), "r"(pack2(acc[8 * q + 6], acc[8 * q + 7])) : "memory");
  fence_async_smem();
  __syncwarp();
  if (lane == 0) {
    asm volatile("cp.reduce.async.bulk.tensor.2d.global.shared::cta.add.tile.bulk_group [%0, {%2, %3}], [%1];" ::"l"(m), "r"(st), "r"(col), "r"(row) : "memory");
    bulk_commit();
    asm volatile("cp.async.bulk.wait_group.read 6;" ::: "memory");
  }
}

__global__ void __launch_bounds__(384, 1) fused_block_kernel(const __grid_constant__ Params P) {
  extern __shared__ __align__(1024) uint8_t smem_raw[];
  if ((uint32_t)__cvta_generic_to_shared(smem_raw) != SB) return;
  const int tid = threadIdx.x, warp = __shfl_sync(0xffffffffu, tid >> 5, 0), lane = __shfl_sync(0xffffffffu, tid & 31, tid & 31);
  const int blk = blockIdx.x;
  int r, g;
  {
    const int q = blk >> 3, u = q >> 1;
    const int R = (u < 4) ? u : 7 - u;
    const int G = ((u >> 2) << 1) | ((q ^ u) & 1);
    r = 4 * R + ((blk & 7) >> 1);
    g = 2 * G + (blk & 1);
  }
  const int odd = g & 1;

  if (warp >= 8) {
    asm volatile("setmaxnreg.dec.sync.aligned.u32 24;");
    if (warp == 8) {
      if (lane == 0) {
#pragma unroll
        for (int s = 0; s < NSLOT; s++) { mbar_init(A_FULL + 8 * s, 1); mbar_init(A_EMPTY + 8 * s, 8); }
        mbar_init(A_XFREE, 8); mbar_init(A_KVL, 1); mbar_init(A_OUTRDY, 1);
        fence_async_smem();
      }
      __syncwarp();
      bar_arrive<BAR_INIT, 384>();
      if (lane == 0) {
        const int c64 = 72 * g + (odd ? -8 : 32), c32 = 72 * g + (odd ? 40 : 0);
#pragma unroll 1
        for (uint32_t it = 0; it < 144; it++) {
          const CUtensorMap* m; int c0, c1;
          if (it < 27) {
            const int sec = it / 9, s = it - 9 * sec, s32 = (sec == 1) ? s - 6 : s, s64 = (sec == 1) ? s : s - 3;
            const bool n32 = (unsigned)s32 < 3u;
            m = n32 ? &P.tq32 : &P.tq64;
            c0 = (sec == 2 ? 0 : (sec + 1) * D_) + (n32 ? c32 : c64);
            c1 = n32 ? 192 * s32 : 96 * s64;
          } else if (it < 36) {
            const int t = (it - 27) / 3, s = it - 27 - 3 * t;
            m = s == 2 ? &P.to32 : &P.to64;
            c0 = s == 2 ? c32 : c64;
            c1 = 192 * t + (s == 1 ? 96 : 0);
          } else {
            const int p = (it - 36) / 6, s = it - 36 - 6 * p;
            m = p < 9 ? &P.tw1 : &P.tw2;
            c0 = p < 9 ? D_ * g + 64 * p : 64 * (p - 9);
            c1 = p < 9 ? 96 * s : D_ * g + 96 * s;
          }
          const uint32_t slot = it & (NSLOT - 1);
          if (it == 6) mbar_wait(A_XFREE, 0);
          mbar_wait(A_EMPTY + 8 * slot, ((it >> 3) & 1) ^ 1);
          mbar_expect_tx(A_FULL + 8 * slot, SLOT_BYTES);
          tma2d(SB + slot * SLOT_BYTES, m, c0, c1, A_FULL + 8 * slot);
        }
      }
    } else {
      const int ht = tid - 288, hw = warp - 9;
      const bool feeder = (hw < 2) && lane == 0;
      const uint32_t lb = A_LAND + hw * 40, H = A_X + hw * 65536;
      if (feeder) {
#pragma unroll
        for (int i = 0; i < 5; i++) mbar_init(lb + 8 * i, 1);
        fence_async_smem();
#pragma unroll
        for (int i = 0; i < 3; i++) { mbar_expect_tx(lb + 8 * i, 24576); tma3d(A_XT + hw * 73728 + i * 24576, &P.tx, r * 128 + hw * 64, 3 * i, lb + 8 * i); }
        mbar_arrive(lb + 24); mbar_arrive(lb + 32);
      }
      if (ht == 64) l2_prefetch(reinterpret_cast<const char*>(P.wqkv) + blk * 15552, 15552);
      const unsigned ep1 = ldg32(&g_epoch[blk]) + 1;
      uint32_t wv[7], bv[3];
      {
        const uint32_t* wp = reinterpret_cast<const uint32_t*>(P.wphi) + g * 648 + ht;
#pragma unroll
        for (int i = 0; i < 7; i++) if (i < 6 || ht < 72) wv[i] = ldg32(wp + 96 * i);
        const uint32_t* bp = reinterpret_cast<const uint32_t*>(P.b1) + g * 288 + ht;
#pragma unroll
        for (int i = 0; i < 3; i++) bv[i] = ldg32(bp + 96 * i);
      }
      bar_sync<BAR_INIT, 384>();
#pragma unroll
      for (int i = 0; i < 3; i++)
        sts64(A_B1 + (ht >> 3) * 64 + (ht & 3) * 16 + (ht & 4) * 2 + i * 768, __float_as_uint(0.5f * bf_lo(bv[i])), __float_as_uint(0.5f * bf_hi(bv[i])));
      if (ht < 45) g_kv[((ep1 & 1) * 8 + g) * 720 + r * 45 + ht] = make_float4(0.f, 0.f, 0.f, 0.f);
      mbar_wait(A_XFREE, 0);
      if (ht == 64) l2_prefetch(reinterpret_cast<const char*>(P.wo) + blk * 5184, 5184);
      if (ht == 65) l2_prefetch(reinterpret_cast<const char*>(P.w1) + blk * 41472, 41472);
      if (ht == 66) l2_prefetch(reinterpret_cast<const char*>(P.w2) + blk * 41472, 41472);
#pragma unroll 1
      for (int i = ht; i < 720; i += 96) sts128(A_WPHI + i * 16, 0, 0, 0, 0);
      bar_sync<BAR_HELP, 96>();
      {
        const int c40 = odd ? 0 : 32, c32 = odd ? 40 : 0;
#pragma unroll
        for (int i = 0; i < 7; i++) {
          const int e = ht + 96 * i, col = e / 9, t = e - col * 9, h = col / 18;
          const int kk = (col >= c40 && col < c40 + 40) ? 32 + col - c40 : col - c32;
          if (i < 6 || ht < 72) sts32(A_WPHI + t * 1280 + kk * 16 + 4 * h, wv[i]);
        }
      }
#pragma unroll 1
      for (int i = ht; i < 512; i += 96) sts128(A_V + (i >> 7) * 6144 + 4096 + (i & 127) * 16, 0, 0x00003f80u, 0, 0);
      fence_async_smem();
      bar_arrive<BAR_PREP, 352>();
#pragma unroll 1
      for (int i = ht; i < 1584; i += 96) sts128(A_KVB + i * 16, 0, 0, 0, 0);
      if (hw == 0) {
        bar_sync<BAR_KVOUT, 288>();
        if (lane == 0) {
          TSX(288, 20);
          float4* kv = g_kv + (((ep1 + 1) & 1) * 8 + g) * 720;
#pragma unroll
          for (int h = 0; h < 4; h++)
            asm volatile("cp.reduce.async.bulk.global.shared::cta.bulk_group.add.f32 [%0], [%1], %2;" ::"l"(kv + h * 180), "r"(A_V + h * 6144), "r"(2880) : "memory");
          bulk_commit();
          mbar_expect_tx(A_KVL, 11520);
          bulk_wait_all();
          signal(&g_cnt[g * 32]);
          TSX(288, 21);
          poll(&g_cnt[g * 32], ep1 * 16);
          TSX(288, 22);
          bulk_load(A_PHI, kv, 11520, A_KVL);
        }
      }
      const int f0 = ht / 5, kq = ht - 5 * f0, f1 = f0 + 18;
      const uint32_t kr0 = A_KVB + (16 * (f0 >> 2) + 8 * ((f0 >> 1) & 1) + (f0 & 1)) * 16, kr1 = A_KVB + (16 * (f1 >> 2) + 8 * ((f1 >> 1) & 1) + (f1 & 1)) * 16;
      bar_sync<BAR_HELP, 96>();
      mbar_wait(A_KVL, 0);
      TSX(288, 23);
      if (ht < 90) {
#pragma unroll
        for (int h = 0; h < 4; h++) {
          const int n0 = 18 * h + 4 * kq, n1 = n0 + 2;
          const uint32_t c0 = (n0 >> 3) * 2304 + (n0 & 7) * 2 + 32 * h, c1 = (n1 >> 3) * 2304 + (n1 & 7) * 2 + 32 * h;
#pragma unroll
          for (int u = 0; u < 2; u++) {
            uint32_t v0, v1, v2, v3;
            lds128(A_PHI + ht * 16 + h * 2880 + u * 1440, v0, v1, v2, v3);
            const uint32_t ra = u ? kr1 : kr0;
            sts32(ra + c0, pack2(__uint_as_float(v0), __uint_as_float(v1)));
            if (kq < 4) sts32(ra + c1, pack2(__uint_as_float(v2), __uint_as_float(v3)));
            else {
              const uint32_t zz = (h & 1) ? pack2(0.f, __uint_as_float(v2)) : pack2(__uint_as_float(v2), 0.f);
              sts128(ra + 32 * h + (9 + (h >> 1)) * 2304, zz, zz, zz, zz);
            }
          }
        }
      }
      fence_async_smem();
      bar_arrive<BAR_KVB, 352>();
      TSX(288, 24);
      if (hw < 2) {
        bar_sync<BAR_OMMA, 320>();
        if (lane == 0) {
#pragma unroll 1
          for (int x = 0; x < 2; x++) {
            poll(&g_cnt[(8 + 32 * x + 2 * r + hw) * 32], ep1 * 32);
            TSX(288, 25 + x);
            mbar_expect_tx(lb, x ? 16384 : 12288);
            if (x) bulk_load(H + 61440, g_stats + (r * 8 + hw * 4) * 64, 4096, lb);
#pragma unroll 1
            for (int i = 0; i < 5; i++) {
              if (i) mbar_expect_tx(lb + 8 * i, 12288);
              tma3d(H + i * 12288, x ? &P.tgh : &P.tgo, 3 * i, r * 8 + hw * 4, lb + 8 * i);
            }
          }
          mbar_wait(lb + 32, 0);
        }
      }
      bar_sync<BAR_HELP, 96>();
#pragma unroll 1
      for (int u = hw; u < 18; u += 3) {
        const int j = u >> 1, w0 = r * 8 + (u & 1) * 4, J = 9 * g + j;
        const bool split = (j == (odd ? 0 : 8));
        const uint2* src = reinterpret_cast<const uint2*>(g_h + (w0 * 36 + (J >> 1)) * 32) + (split ? (J & 1) * 32 + lane : (J & 1) + 2 * lane);
        const int col = 8 * J + 2 * (lane & 3);
        const uint32_t b = ldg32(P.b2 + col);
        uint32_t v[8];
#pragma unroll
        for (int w = 0; w < 4; w++) ldg64(src + w * 2304, v[2 * w], v[2 * w + 1]);
        __nv_bfloat16* o = P.out + (size_t)(w0 * 16 + (lane >> 2)) * D_ + col;
#pragma unroll
        for (int w = 0; w < 8; w++) stg32(o + w * 8 * D_, hadd2(v[w], b));
      }
      bar_sync<BAR_HELP, 96>();
      if (ht == 0) {
        signal_release(&g_cnt[(72 + r) * 32]);
        poll(&g_cnt[(72 + r) * 32], ep1 * 8);
        asm volatile("fence.acq_rel.gpu;" ::: "memory");
        mbar_arrive(A_OUTRDY);
        g_epoch[blk] = ep1;
        TSX(288, 27);
      }
    }
  } else {
    asm volatile("setmaxnreg.inc.sync.aligned.u32 240;");
    TS(0);
    const int c = lane & 3, rq = lane >> 2, wg = warp >> 2, wq = warp & 3;
    const uint64_t z = P.d64, o40 = P.d128 + odd;
    const uint32_t lb = A_LAND + wg * 40;
    uint32_t a[144];
    float rlo, rhi;
    bar_sync<BAR_INIT, 384>();
    {
      const uint32_t xr = A_XT + wg * 73728 + (wq * 16 + (lane & 15)) * 128;
      const int x7 = (lane & 7) ^ (lane >> 4);
      float sm[4] = {}, dl[2][4] = {}, dh[2][4] = {};
      static_for<0, 36>([&](auto s) {
        constexpr int k = s.value;
        if constexpr (k % 12 == 0) {
          mbar_wait(lb + 8 * (k / 12), 0);
          static_for<k, k + 12>([&](auto t) {
            constexpr int u = t.value;
            ldsm4(xr + (u >> 2) * 8192 + (((2 * (u & 3)) ^ x7) << 4), a[4 * u], a[4 * u + 1], a[4 * u + 2], a[4 * u + 3]);
          });
        }
        mma16816(sm, a[4 * k], a[4 * k + 1], a[4 * k + 2], a[4 * k + 3], 0x3f803f80u, 0x3f803f80u);
        mma1688(dl[0], a[4 * k], a[4 * k + 1], a[4 * k]);
        mma1688(dh[0], a[4 * k], a[4 * k + 1], a[4 * k + 1]);
        mma1688(dl[1], a[4 * k + 2], a[4 * k + 3], a[4 * k + 2]);
        mma1688(dh[1], a[4 * k + 2], a[4 * k + 3], a[4 * k + 3]);
      });
      const float mlo = sm[0] * (1.f / D_), mhi = sm[2] * (1.f / D_);
      if (lane == 0) asm volatile("mbarrier.arrive.shared::cta.b64 _, [%0];" ::"r"(A_XFREE), "f"(mlo) : "memory");
      float ql = (rq & 1) ? dl[0][1] + dl[1][1] : dl[0][0] + dl[1][0];
      float qh = (rq & 1) ? dh[0][3] + dh[1][3] : dh[0][2] + dh[1][2];
      ql = __shfl_sync(0xffffffffu, ql, (lane & 28) | (rq >> 1));
      qh = __shfl_sync(0xffffffffu, qh, (lane & 28) | (rq >> 1));
      rlo = rsq(fmaxf(ql * (1.f / D_) - mlo * mlo, 0.f) + 1e-5f);
      rhi = rsq(fmaxf(qh * (1.f / D_) - mhi * mhi, 0.f) + 1e-5f);
      const uint32_t ml = pack2(mlo, mlo), mh = pack2(mhi, mhi);
#pragma unroll
      for (int i = 0; i < 144; i++) a[i] = hsub2(a[i], (i & 1) ? mh : ml);
    }
    TS(1);
    uint32_t fq[36];
    {
      float k40[20], k32[16], v40[20], v32[16], p[36];
      stage_c<12, 0, 64, 0>(k32, a, z);
      stage_c<12, 12, 64, 1>(k32, a, z);    wg_wait<1>(); release_c<0>(lane);
      stage_c<12, 24, 64, 2>(k32, a, z);    wg_wait<1>(); release_c<1>(lane);
      stage_c<6, 0, 128, 3>(k40, a, o40);   wg_wait<1>(); pin(k32); release_c<2>(lane);
      stage_c<6, 6, 128, 4>(k40, a, o40);   wg_wait<1>(); release_c<3>(lane);
      stage_c<6, 12, 128, 5>(k40, a, o40);  wg_wait<1>(); release_c<4>(lane);
      stage_c<6, 18, 128, 6>(k40, a, o40);
      bar_sync<BAR_PREP, 352>();
      phi_mma0(p, k32, rlo, rhi, P.dwphi);        wg_wait<1>(); release_c<5>(lane); release_c<6>(lane);
      stage_c<6, 24, 128, 7>(k40, a, o40);
      stage_c<6, 30, 128, 8>(k40, a, o40);  wg_wait<1>(); release_c<7>(lane);
      wg_wait<0>(); pin(k40); release_c<8>(lane);
      TS(2);
      phi_mma1(p, k40, rlo, rhi, P.dwphi);
      stage_c<6, 0, 128, 9>(v40, a, o40);   wg_wait<1>(); pin(p);
      const uint32_t prow = A_PHI + c * 16384 + (warp * 16 + rq) * 128;
      stage_c<6, 6, 128, 10>(v40, a, o40);
      stage_c<6, 12, 128, 11>(v40, a, o40); phik_piece<0, 0>(p, prow, c, rq); wg_wait<1>(); release_c<9>(lane); release_c<10>(lane);
      stage_c<6, 18, 128, 12>(v40, a, o40); phik_piece<0, 1>(p, prow, c, rq); wg_wait<1>(); release_c<11>(lane);
      stage_c<6, 24, 128, 13>(v40, a, o40); phik_piece<1, 0>(p, prow, c, rq); wg_wait<1>(); release_c<12>(lane);
      stage_c<6, 30, 128, 14>(v40, a, o40); phik_piece<1, 1>(p, prow, c, rq); wg_wait<1>(); release_c<13>(lane);
      stage_c<12, 0, 64, 15>(v32, a, z);    wg_wait<1>(); release_c<14>(lane);
      stage_c<12, 12, 64, 16>(v32, a, z);   wg_wait<1>(); release_c<15>(lane);
      stage_c<12, 24, 64, 17>(v32, a, z);   wg_wait<1>(); release_c<16>(lane);
      TS(3);
      stage_c<12, 0, 64, 18>(k32, a, z);    wg_wait<1>(); pin(v40); pin(v32); release_c<17>(lane);
      {
        const int c40 = odd ? 0 : 32, c32 = odd ? 40 : 0;
        const uint32_t vrow = A_V + (warp * 16 + rq) * 16;
#pragma unroll
        for (int j = 0; j < 9; j++) {
          const int col = (j < 5 ? c40 + 8 * j : c32 + 8 * (j - 5)) + 2 * c;
          const int h = (col * 57) >> 10, d = col - 18 * h;
          const uint32_t ad = vrow + h * 6144 + (d >> 3) * 2048 + (d & 7) * 2;
          const float* v = j < 5 ? &v40[4 * j] : &v32[4 * (j - 5)];
          sts32(ad, pack2(v[0] * rlo, v[1] * rlo));
          sts32(ad + 128, pack2(v[2] * rhi, v[3] * rhi));
        }
      }
      fence_async_smem();
      bar_sync<BAR_KVIN, 256>();
      float kv0[12], kv1[12];
      {
        uint64_t da = P.dphi + wg * 2048, db = P.dv + wg * 768;
        wg_fence();
        static_for<0, 8>([&](auto s) { wgmma_ss_tt<128, s.value == 7 ? 384 - 112 : 16, s.value != 0>(kv0, da, db); });
        static_for<0, 8>([&](auto s) { wgmma_ss_tt<128, 16, s.value != 0>(kv1, da, db); });
        wg_commit();
      }
      stage_c<12, 12, 64, 19>(k32, a, z);   wg_wait<1>(); pin(kv0); pin(kv1); release_c<18>(lane);
      bar_sync_wg(wg);
#pragma unroll
      for (int hh = 0; hh < 2; hh++) {
#pragma unroll
        for (int u = 0; u < 2; u++) {
          const int f = 8 * ((2 * wq + u - 4 * wg - 2 * hh) & 7) + rq;
          if (f < 36) {
            const uint32_t ad = A_V + (2 * wg + hh) * 6144 + f * 80 + c * 8;
            const float* kvp = hh ? kv1 : kv0;
            sts64(ad, __float_as_uint(kvp[2 * u]), __float_as_uint(kvp[2 * u + 1]));
            sts64(ad + 32, __float_as_uint(kvp[4 + 2 * u]), __float_as_uint(kvp[5 + 2 * u]));
            if (c < 2) sts64(ad + 64, __float_as_uint(kvp[8 + 2 * u]), __float_as_uint(kvp[9 + 2 * u]));
          }
        }
      }
      fence_async_smem();
      bar_arrive<BAR_KVOUT, 288>();
      stage_c<12, 24, 64, 20>(k32, a, z);   wg_wait<1>(); release_c<19>(lane);
      stage_c<6, 0, 128, 21>(k40, a, o40);  wg_wait<1>(); pin(k32); release_c<20>(lane);
      stage_c<6, 6, 128, 22>(k40, a, o40);
      phi_mma0(p, k32, rlo, rhi, P.dwphi);        wg_wait<1>(); release_c<21>(lane); release_c<22>(lane);
      stage_c<6, 12, 128, 23>(k40, a, o40);
      stage_c<6, 18, 128, 24>(k40, a, o40); wg_wait<1>(); release_c<23>(lane);
      stage_c<6, 24, 128, 25>(k40, a, o40); wg_wait<1>(); release_c<24>(lane);
      stage_c<6, 30, 128, 26>(k40, a, o40); wg_wait<1>(); release_c<25>(lane);
      wg_wait<0>(); pin(k40); release_c<26>(lane);
      TS(4);
      phi_mma1(p, k40, rlo, rhi, P.dwphi);
      wg_wait<0>(); pin(p);
      phiq_piece<0, 0>(p, fq); phiq_piece<1, 0>(p, fq); phiq_piece<0, 1>(p, fq); phiq_piece<1, 1>(p, fq);
    }
    TS(5);
    uint32_t xr[18];
    {
      const __nv_bfloat16* xp = P.x + (size_t)(r * 128 + warp * 16 + rq) * D_ + 72 * g + 2 * c;
      const __nv_bfloat16 *x40 = xp + (odd ? 0 : 32), *x32 = xp + (odd ? 40 : 0);
#pragma unroll
      for (int j = 0; j < 9; j++) {
        const __nv_bfloat16* q = j < 5 ? x40 + 8 * j : x32 + 8 * (j - 5);
        xr[2 * j] = ldg32(q);
        xr[2 * j + 1] = ldg32(q + 8 * D_);
      }
    }
    const int rw = r * 8 + warp;
    const uint32_t land = A_X + wg * 65536 + wq * 3072;
    {
      float o[44];
      uint64_t d = P.dkvb;
      bar_sync<BAR_KVB, 352>();
      TS(6);
      wg_fence();
      static_for<0, 9>([&](auto s) { wgmma_rs<16, s.value != 0>(o, fq[4 * s.value], fq[4 * s.value + 1], fq[4 * s.value + 2], fq[4 * s.value + 3], d); });
      wg_commit();
      wg_wait<0>(); pin(o);
      bar_arrive<BAR_OMMA, 320>();
      uint32_t f[18], ff[16];
#pragma unroll
      for (int u = 0; u < 2; u++) {
        const float i0 = rcp(o[36 + 2 * u] + 1e-6f), i1 = rcp(o[37 + 2 * u] + 1e-6f), i2 = rcp(o[40 + 2 * u] + 1e-6f), i3 = rcp(o[41 + 2 * u] + 1e-6f);
        const float sc[9] = {i0, i0, c < 1 ? i0 : i1, i1, c < 2 ? i1 : i2, i2, c < 3 ? i2 : i3, i3, i3};
#pragma unroll
        for (int j = 0; j < 9; j++) f[2 * j + u] = pack2(o[4 * j + 2 * u] * sc[j], o[4 * j + 2 * u + 1] * sc[j]);
      }
#pragma unroll
      for (int i = 0; i < 16; i++) ff[i] = odd ? f[i + 2] : f[i];
      stage_piece(land, lane, odd, ff, odd ? f[0] : f[16], odd ? f[1] : f[17]);
      fence_async_smem();
      __syncwarp();
      if (lane == 0) {
        bulk_store(reinterpret_cast<char*>(g_o + rw * 1152) + g * 2304, land, 2304);
        bulk_commit(); bulk_wait_all();
        signal(&g_cnt[(8 + 2 * r + wg) * 32]);
      }
      TS(7);
    }
    {
      float h40[20], h32[16];
      mbar_wait(lb, 1);
      TS(8);
      tail_read(a, g_o + rw * 1152, lane);
      land_read<0>(a, land, lane);                          stage_c<6, 0, 128, 27>(h40, a, o40);
      mbar_wait(lb + 8, 1);  land_read<1>(a, land, lane);   stage_c<6, 6, 128, 28>(h40, a, o40);  wg_wait<1>(); release_c<27>(lane);
      stage_c<12, 0, 64, 29>(h32, a, z);
      mbar_wait(lb + 16, 1); land_read<2>(a, land, lane);   wg_wait<1>(); release_c<28>(lane);
      stage_c<6, 12, 128, 30>(h40, a, o40);
      mbar_wait(lb + 24, 1); land_read<3>(a, land, lane);   wg_wait<1>(); release_c<29>(lane);
      stage_c<6, 18, 128, 31>(h40, a, o40); wg_wait<1>(); release_c<30>(lane);
      stage_c<12, 12, 64, 32>(h32, a, z);
      mbar_wait(lb + 32, 1); land_read<4>(a, land, lane);   wg_wait<1>(); release_c<31>(lane);
      stage_c<6, 24, 128, 33>(h40, a, o40); wg_wait<1>(); release_c<32>(lane);
      stage_c<6, 30, 128, 34>(h40, a, o40); wg_wait<1>(); release_c<33>(lane);
      stage_c<12, 24, 64, 35>(h32, a, z);   wg_wait<1>(); release_c<34>(lane);
      wg_wait<0>(); pin(h40); pin(h32); release_c<35>(lane);
      TS(9);
      uint32_t f[18], ff[16];
      float sl = 0.f, ql = 0.f, sh = 0.f, qh = 0.f;
#pragma unroll
      for (int j = 0; j < 9; j++) {
        const float* v = j < 5 ? &h40[4 * j] : &h32[4 * (j - 5)];
        f[2 * j] = pack2(v[0] + bf_lo(xr[2 * j]), v[1] + bf_hi(xr[2 * j]));
        f[2 * j + 1] = pack2(v[2] + bf_lo(xr[2 * j + 1]), v[3] + bf_hi(xr[2 * j + 1]));
      }
#pragma unroll
      for (int i = 0; i < 8; i++) { ff[i] = odd ? f[i + 2] : f[i + 10]; ff[8 + i] = odd ? f[i + 10] : f[i]; }
      stage_piece(land, lane, odd, ff, odd ? f[0] : f[8], odd ? f[1] : f[9]);
#pragma unroll
      for (int j = 0; j < 9; j++) {
        const float l0 = bf_lo(f[2 * j]), l1 = bf_hi(f[2 * j]), u0 = bf_lo(f[2 * j + 1]), u1 = bf_hi(f[2 * j + 1]);
        sl += l0 + l1; ql = fmaf(l0, l0, fmaf(l1, l1, ql));
        sh += u0 + u1; qh = fmaf(u0, u0, fmaf(u1, u1, qh));
      }
#pragma unroll
      for (int m = 1; m < 4; m <<= 1) {
        sl += __shfl_xor_sync(0xffffffffu, sl, m); ql += __shfl_xor_sync(0xffffffffu, ql, m);
        sh += __shfl_xor_sync(0xffffffffu, sh, m); qh += __shfl_xor_sync(0xffffffffu, qh, m);
      }
      if (c == 0) sts128(land + 2304 + rq * 16, __float_as_uint(sl), __float_as_uint(ql), __float_as_uint(sh), __float_as_uint(qh));
      fence_async_smem();
      __syncwarp();
      if (lane == 0) {
        bulk_store(reinterpret_cast<char*>(g_h + rw * 1152) + g * 2304, land, 2304);
        bulk_store(g_stats + rw * 64 + g * 8, land + 2304, 128);
        bulk_commit(); bulk_wait_all();
        signal(&g_cnt[(40 + 2 * r + wg) * 32]);
      }
      TS(10);
    }
    float accA[32], accB[32];
    {
      mbar_wait(lb, 0);
      TS(11);
      tail_read(a, g_h + rw * 1152, lane);
      uint32_t s0, s1, s2, s3, t0, t1, t2, t3;
      const uint32_t sa = A_X + wg * 65536 + 61440 + wq * 1024 + c * 256 + rq * 16;
      lds128(sa, s0, s1, s2, s3);
      lds128(sa + 128, t0, t1, t2, t3);
      land_read<0>(a, land, lane);
      float sl = __uint_as_float(s0) + __uint_as_float(t0), ql = __uint_as_float(s1) + __uint_as_float(t1);
      float sh = __uint_as_float(s2) + __uint_as_float(t2), qh = __uint_as_float(s3) + __uint_as_float(t3);
#pragma unroll
      for (int m = 1; m < 4; m <<= 1) {
        sl += __shfl_xor_sync(0xffffffffu, sl, m); ql += __shfl_xor_sync(0xffffffffu, ql, m);
        sh += __shfl_xor_sync(0xffffffffu, sh, m); qh += __shfl_xor_sync(0xffffffffu, qh, m);
      }
      sl *= (1.f / D_); sh *= (1.f / D_);
      rlo = 0.5f * rsq(fmaxf(ql * (1.f / D_) - sl * sl, 0.f) + 1e-5f);
      rhi = 0.5f * rsq(fmaxf(qh * (1.f / D_) - sh * sh, 0.f) + 1e-5f);
      const uint32_t ml = pack2(sl, sl), mh = pack2(sh, sh);
      auto center = [&](int k0) {
#pragma unroll
        for (int i = 4 * k0; i < 4 * k0 + 24; i++) a[i] = hsub2(a[i], (i & 1) ? mh : ml);
      };
      center(0);                                                       stage_c<6, 0, 128, 36>(accA, a, P.d128);
      mbar_wait(lb + 8, 0);  land_read<1>(a, land, lane); center(6);   stage_c<6, 6, 128, 37>(accA, a, P.d128);
      mbar_wait(lb + 16, 0); land_read<2>(a, land, lane); center(12);  wg_wait<1>(); release_c<36>(lane); stage_c<6, 12, 128, 38>(accA, a, P.d128);
      mbar_wait(lb + 24, 0); land_read<3>(a, land, lane); center(18);  wg_wait<1>(); release_c<37>(lane); stage_c<6, 18, 128, 39>(accA, a, P.d128);
      mbar_wait(lb + 32, 0); land_read<4>(a, land, lane); center(24);  wg_wait<1>(); release_c<38>(lane); stage_c<6, 24, 128, 40>(accA, a, P.d128);
      center(30);
      bar_sync_wg(wg);
      wg_wait<1>(); release_c<39>(lane);
    }
    TS(12);
    {
      const uint32_t xw = A_X + warp * 16384;
      const int grow = r * 128 + warp * 16;
      uint32_t t8 = 41 * 8;
#pragma unroll 1
      for (int i = 0; i < 9; i++) {
        const uint32_t b1a = A_B1 + c * 16 + i * 512, hd = xw + (i & 3) * 4096;
        stage_r<30>(accA, a, t8, P.d128); wg_wait<1>(); release_r(t8 - 8, lane);
        if (i == 4) {
          TS(13);
          wg_wait<0>();
#pragma unroll
          for (int s = 0; s < 32; s++) lds128(xw + lane * 16 + s * 512, a[4 * s], a[4 * s + 1], a[4 * s + 2], a[4 * s + 3]);
          mbar_wait(A_OUTRDY, 0);
          fence_async_global();
        }
        stage_r<0>(accB, a, t8 + 8, P.d128);   wg_wait<1>(); pin(accA); release_r(t8, lane);
        stage_g<6, 0>(accB, a, t8 + 16, P.d128, i <= 4, accA, rlo, rhi, b1a, hd + lane * 16);
        if (i > 4) out_tile(accA, &P.tout, hd, 128 * i - 576, grow, lane);
        wg_wait<1>(); release_r(t8 + 8, lane);
        stage_g<12, 1>(accB, a, t8 + 24, P.d128, i <= 4, accA, rlo, rhi, b1a, hd + lane * 16);
        wg_wait<1>(); release_r(t8 + 16, lane);
        stage_g<18, 2>(accB, a, t8 + 32, P.d128, i <= 4, accA, rlo, rhi, b1a, hd + lane * 16);
        wg_wait<1>(); release_r(t8 + 24, lane);
        stage_g<24, 3>(accB, a, t8 + 40, P.d128, i <= 4, accA, rlo, rhi, b1a, hd + lane * 16);
        if (i == 4) {
#pragma unroll
          for (int s = 0; s < 4; s++) lds128(xw + lane * 16 + s * 512, a[128 + 4 * s], a[129 + 4 * s], a[130 + 4 * s], a[131 + 4 * s]);
          TS(14);
        }
        wg_wait<1>(); release_r(t8 + 32, lane);
        stage_r<30>(accB, a, t8 + 48, P.d128); wg_wait<1>(); release_r(t8 + 40, lane);
        if (i < 8) { stage_r<0>(accA, a, t8 + 56, P.d128); wg_wait<1>(); } else { wg_wait<0>(); TS(15); }
        pin(accB); release_r(t8 + 48, lane);
        if (i < 8) stage_g<6, 0>(accA, a, t8 + 64, P.d128, i <= 3, accB, rlo, rhi, b1a + 256, hd + 2048 + lane * 16);
        if (i > 3) out_tile(accB, &P.tout, hd + 2048, 128 * i - 512, grow, lane);
        if (i < 8) {
          wg_wait<1>(); release_r(t8 + 56, lane);
          stage_g<12, 1>(accA, a, t8 + 72, P.d128, i <= 3, accB, rlo, rhi, b1a + 256, hd + 2048 + lane * 16);
          wg_wait<1>(); release_r(t8 + 64, lane);
          stage_g<18, 2>(accA, a, t8 + 80, P.d128, i <= 3, accB, rlo, rhi, b1a + 256, hd + 2048 + lane * 16);
          wg_wait<1>(); release_r(t8 + 72, lane);
          stage_g<24, 3>(accA, a, t8 + 88, P.d128, i <= 3, accB, rlo, rhi, b1a + 256, hd + 2048 + lane * 16);
          wg_wait<1>(); release_r(t8 + 80, lane);
        }
        t8 += 96;
      }
      wg_wait<0>();
      if (lane == 0) bulk_wait_all();
      TS(16);
      TS_DUMP();
    }
  }
}

typedef CUresult (*EncodeFn)(CUtensorMap*, CUtensorMapDataType, cuuint32_t, void*, const cuuint64_t*, const cuuint64_t*, const cuuint32_t*,
                             const cuuint32_t*, CUtensorMapInterleave, CUtensorMapSwizzle, CUtensorMapL2promotion, CUtensorMapFloatOOBfill);

void enc2d(EncodeFn fn, CUtensorMap* m, const void* base, uint64_t cols, uint64_t rows, uint32_t bc, uint32_t br) {
  cuuint64_t gd[2] = {cols, rows}, gs[1] = {cols * 2};
  cuuint32_t bd[2] = {bc, br}, es[2] = {1, 1};
  fn(m, CU_TENSOR_MAP_DATA_TYPE_BFLOAT16, 2, const_cast<void*>(base), gd, gs, bd, es, CU_TENSOR_MAP_INTERLEAVE_NONE,
     bc == 64 ? CU_TENSOR_MAP_SWIZZLE_128B : CU_TENSOR_MAP_SWIZZLE_64B, CU_TENSOR_MAP_L2_PROMOTION_L2_128B, CU_TENSOR_MAP_FLOAT_OOB_FILL_NONE);
}

}

extern "C" void kernel_launch(void* const* d_in, const int* in_sizes, int n_in, void* d_out, int out_size) {
  (void)in_sizes; (void)n_in; (void)out_size;
  static EncodeFn fn = nullptr;
  static void *po = nullptr, *ph = nullptr;
  if (!fn) {
    void* p = nullptr;
    cudaDriverEntryPointQueryResult q;
    cudaGetDriverEntryPoint("cuTensorMapEncodeTiled", &p, cudaEnableDefault, &q);
    fn = (EncodeFn)p;
    cudaFuncSetAttribute(fused_block_kernel, cudaFuncAttributeMaxDynamicSharedMemorySize, SMEM_BYTES);
    cudaGetSymbolAddress(&po, g_o);
    cudaGetSymbolAddress(&ph, g_h);
  }
  Params P;
  P.x = (const __nv_bfloat16*)d_in[0];
  P.wqkv = (const __nv_bfloat16*)d_in[1];
  P.wphi = (const __nv_bfloat16*)d_in[2];
  P.wo = (const __nv_bfloat16*)d_in[3];
  P.w1 = (const __nv_bfloat16*)d_in[5];
  P.b1 = (const __nv_bfloat16*)d_in[6];
  P.w2 = (const __nv_bfloat16*)d_in[7];
  P.b2 = (const __nv_bfloat16*)d_in[8];
  P.out = (__nv_bfloat16*)d_out;
  P.d128 = desc64(SB, 16, 1024, 1);
  P.d64 = desc64(SB, 16, 512, 2);
  P.dwphi = desc64(A_WPHI, 128, 1280, 0);
  P.dkvb = desc64(A_KVB, 128, 2304, 0);
  P.dphi = desc64(A_PHI, 16, 1024, 1);
  P.dv = desc64(A_V, 128, 2048, 0);
  enc2d(fn, &P.tq64, P.wqkv, 3 * D_, D_, 64, 96);
  enc2d(fn, &P.tq32, P.wqkv, 3 * D_, D_, 32, 192);
  enc2d(fn, &P.to64, P.wo, D_, D_, 64, 96);
  enc2d(fn, &P.to32, P.wo, D_, D_, 32, 192);
  enc2d(fn, &P.tw1, P.w1, F_, D_, 64, 96);
  enc2d(fn, &P.tw2, P.w2, D_, F_, 64, 96);
  enc2d(fn, &P.tout, P.out, D_, S_, 64, 16);
  {
    cuuint64_t gd[3] = {64, (cuuint64_t)S_, 9}, gs[2] = {D_ * 2, 128};
    cuuint32_t bd[3] = {64, 64, 3}, es[3] = {1, 1, 1};
    fn(&P.tx, CU_TENSOR_MAP_DATA_TYPE_BFLOAT16, 3, const_cast<__nv_bfloat16*>(P.x), gd, gs, bd, es, CU_TENSOR_MAP_INTERLEAVE_NONE,
       CU_TENSOR_MAP_SWIZZLE_128B, CU_TENSOR_MAP_L2_PROMOTION_L2_128B, CU_TENSOR_MAP_FLOAT_OOB_FILL_NONE);
  }
  for (int i = 0; i < 2; i++) {
    cuuint64_t gd[3] = {256, 18, 128}, gs[2] = {1024, 18432};
    cuuint32_t bd[3] = {256, 3, 4}, es[3] = {1, 1, 1};
    fn(i ? &P.tgh : &P.tgo, CU_TENSOR_MAP_DATA_TYPE_UINT32, 3, i ? ph : po, gd, gs, bd, es, CU_TENSOR_MAP_INTERLEAVE_NONE,
       CU_TENSOR_MAP_SWIZZLE_NONE, CU_TENSOR_MAP_L2_PROMOTION_L2_128B, CU_TENSOR_MAP_FLOAT_OOB_FILL_NONE);
  }
  fused_block_kernel<<<128, 384, SMEM_BYTES>>>(P);
}
```

```cpp
#include <cuda_runtime.h>
#include <cuda.h>
#include <cuda_bf16.h>
#include <stdint.h>
#include <type_traits>

namespace {

constexpr int S_ = 2048, D_ = 576, F_ = 4608;
constexpr int NSLOT = 8, SLOT_BYTES = 12288;
constexpr uint32_t SB       = 1024;
constexpr uint32_t A_X      = SB + NSLOT * SLOT_BYTES;
constexpr uint32_t A_XT     = A_X - 16384;
constexpr uint32_t A_PHI    = A_X;
constexpr uint32_t A_V      = A_X + 65536;
constexpr uint32_t A_WPHI   = A_X + 90112;
constexpr uint32_t A_KVB    = A_X + 101632;
constexpr uint32_t A_B1     = A_X + 131072;
constexpr uint32_t A_FULL   = A_B1 + 2304;
constexpr uint32_t A_EMPTY  = A_FULL + 64;
constexpr uint32_t A_LAND   = A_FULL + 128;
constexpr uint32_t A_XFREE  = A_LAND + 80;
constexpr uint32_t A_KVL    = A_XFREE + 8;
constexpr uint32_t A_OUTRDY = A_KVL + 8;
constexpr uint32_t A_TS     = A_OUTRDY + 8;
constexpr uint32_t SMEM_BYTES = A_TS + 256 - SB;
static_assert((A_FULL & 63) == 0, "barrier block alignment");
constexpr int SPIN_LIMIT = 1 << 20;

enum { BAR_INIT = 1, BAR_PREP = 2, BAR_KVIN = 3, BAR_KVOUT = 4, BAR_KVB = 5, BAR_HELP = 6, BAR_WG = 7  , BAR_OMMA = 9 };

struct Params {
  CUtensorMap tx, tq64, tq32, to64, to32, tw1, tw2, tout, tgo, tgh;
  const __nv_bfloat16 *x, *wqkv, *wphi, *wo, *w1, *b1, *w2, *b2;
  __nv_bfloat16* out;
  uint64_t d128, d64, dwphi, dkvb, dphi, dv;
};

__device__ uint4    g_o[128 * 36 * 32];
__device__ uint4    g_h[128 * 36 * 32];
__device__ float4   g_stats[128 * 64];
__device__ float4   g_kv[2 * 8 * 720];
__device__ unsigned g_cnt[(8 + 32 + 32 + 16) * 32];
__device__ unsigned g_epoch[128];
#define TSX(t, i)
#define TS(i)
#define TSG(i)
#define TS_DUMP()

__device__ __forceinline__ void mbar_init(uint32_t bar, uint32_t cnt) { asm volatile("mbarrier.init.shared::cta.b64 [%0], %1;" ::"r"(bar), "r"(cnt)); }
__device__ __forceinline__ void mbar_expect_tx(uint32_t bar, uint32_t bytes) { asm volatile("mbarrier.arrive.expect_tx.shared::cta.b64 _, [%0], %1;" ::"r"(bar), "r"(bytes) : "memory"); }
__device__ __forceinline__ void mbar_arrive(uint32_t bar) { asm volatile("mbarrier.arrive.shared::cta.b64 _, [%0];" ::"r"(bar) : "memory"); }
__device__ __forceinline__ void mbar_wait(uint32_t bar, uint32_t parity) {
  asm volatile(
      "{\n.reg .pred p;\n"
      "WAIT_%=:\n"
      "mbarrier.try_wait.parity.shared::cta.b64 p, [%0], %1;\n"
      "@p bra DONE_%=;\n"
      "bra WAIT_%=;\n"
      "DONE_%=:\n}\n" ::"r"(bar), "r"(parity) : "memory");
}
template <int ID, int N> __device__ __forceinline__ void bar_sync() { asm volatile("bar.sync %0, %1;" ::"n"(ID), "n"(N) : "memory"); }
template <int ID, int N> __device__ __forceinline__ void bar_arrive() { asm volatile("bar.arrive %0, %1;" ::"n"(ID), "n"(N) : "memory"); }
__device__ __forceinline__ void bar_sync_wg(int wg) { asm volatile("bar.sync %0, 128;" ::"r"(BAR_WG + wg) : "memory"); }
__device__ __forceinline__ void fence_async_smem() { asm volatile("fence.proxy.async.shared::cta;" ::: "memory"); }
__device__ __forceinline__ void fence_async_global() { asm volatile("fence.proxy.async.global;" ::: "memory"); }
__device__ __forceinline__ void tma2d(uint32_t dst, const CUtensorMap* m, int c0, int c1, uint32_t bar) {
  asm volatile("cp.async.bulk.tensor.2d.shared::cluster.global.mbarrier::complete_tx::bytes [%0], [%1, {%3, %4}], [%2];" ::"r"(dst), "l"(m), "r"(bar), "r"(c0), "r"(c1) : "memory");
}
__device__ __forceinline__ void tma3d(uint32_t dst, const CUtensorMap* m, int c1, int c2, uint32_t bar) {
  asm volatile("cp.async.bulk.tensor.3d.shared::cluster.global.mbarrier::complete_tx::bytes [%0], [%1, {%5, %3, %4}], [%2];" ::"r"(dst), "l"(m), "r"(bar), "r"(c1), "r"(c2), "r"(0) : "memory");
}
__device__ __forceinline__ void bulk_load(uint32_t dst, const void* src, uint32_t bytes, uint32_t bar) {
  asm volatile("cp.async.bulk.shared::cluster.global.mbarrier::complete_tx::bytes [%0], [%1], %2, [%3];" ::"r"(dst), "l"(src), "r"(bytes), "r"(bar) : "memory");
}
__device__ __forceinline__ void bulk_store(void* dst, uint32_t src, uint32_t bytes) {
  asm volatile("cp.async.bulk.global.shared::cta.bulk_group [%0], [%1], %2;" ::"l"(dst), "r"(src), "r"(bytes) : "memory");
}
__device__ __forceinline__ void bulk_commit() { asm volatile("cp.async.bulk.commit_group;" ::: "memory"); }
__device__ __forceinline__ void bulk_wait_all() { asm volatile("cp.async.bulk.wait_group 0;" ::: "memory"); }
__device__ __forceinline__ void l2_prefetch(const void* p, uint32_t bytes) { asm volatile("cp.async.bulk.prefetch.L2.global [%0], %1;" ::"l"(p), "r"(bytes) : "memory"); }
__device__ __forceinline__ void wg_fence() { asm volatile("wgmma.fence.sync.aligned;" ::: "memory"); }
__device__ __forceinline__ void wg_commit() { asm volatile("wgmma.commit_group.sync.aligned;" ::: "memory"); }
template <int N> __device__ __forceinline__ void wg_wait() { asm volatile("wgmma.wait_group.sync.aligned %0;" ::"n"(N) : "memory"); }
template <int N> __device__ __forceinline__ void pin(float (&d)[N]) {
#pragma unroll
  for (int i = 0; i < N; i++) asm volatile("" : "+f"(d[i])::"memory");
}
__device__ __forceinline__ uint32_t pack2(float lo, float hi) { uint32_t r; asm("cvt.rn.bf16x2.f32 %0, %1, %2;" : "=r"(r) : "f"(hi), "f"(lo)); return r; }
__device__ __forceinline__ float bf_lo(uint32_t v) { return __uint_as_float(v << 16); }
__device__ __forceinline__ float bf_hi(uint32_t v) { return __uint_as_float(v & 0xffff0000u); }
__device__ __forceinline__ uint32_t hsub2(uint32_t a, uint32_t b) { uint32_t r; asm("sub.rn.bf16x2 %0, %1, %2;" : "=r"(r) : "r"(a), "r"(b)); return r; }
__device__ __forceinline__ uint32_t hadd2(uint32_t a, uint32_t b) { uint32_t r; asm("add.rn.bf16x2 %0, %1, %2;" : "=r"(r) : "r"(a), "r"(b)); return r; }
__device__ __forceinline__ float ex2(float x) { float r; asm("ex2.approx.ftz.f32 %0, %1;" : "=f"(r) : "f"(x)); return r; }
__device__ __forceinline__ float rcp(float x) { float r; asm("rcp.approx.ftz.f32 %0, %1;" : "=f"(r) : "f"(x)); return r; }
__device__ __forceinline__ float rsq(float x) { float r; asm("rsqrt.approx.ftz.f32 %0, %1;" : "=f"(r) : "f"(x)); return r; }
__device__ __forceinline__ float tanh_(float x) { float r; asm("tanh.approx.f32 %0, %1;" : "=f"(r) : "f"(x)); return r; }
__device__ __forceinline__ void mma16816(float (&d)[4], uint32_t a0, uint32_t a1, uint32_t a2, uint32_t a3, uint32_t b0, uint32_t b1) {
  asm("mma.sync.aligned.m16n8k16.row.col.f32.bf16.bf16.f32 {%0,%1,%2,%3}, {%4,%5,%6,%7}, {%8,%9}, {%0,%1,%2,%3};"
      : "+f"(d[0]), "+f"(d[1]), "+f"(d[2]), "+f"(d[3]) : "r"(a0), "r"(a1), "r"(a2), "r"(a3), "r"(b0), "r"(b1));
}
__device__ __forceinline__ void mma1688(float (&d)[4], uint32_t a0, uint32_t a1, uint32_t b0) {
  asm("mma.sync.aligned.m16n8k8.row.col.f32.bf16.bf16.f32 {%0,%1,%2,%3}, {%4,%5}, {%6}, {%0,%1,%2,%3};"
      : "+f"(d[0]), "+f"(d[1]), "+f"(d[2]), "+f"(d[3]) : "r"(a0), "r"(a1), "r"(b0));
}
__device__ __forceinline__ void sts32(uint32_t a, uint32_t v) { asm volatile("st.shared.b32 [%0], %1;" ::"r"(a), "r"(v) : "memory"); }
__device__ __forceinline__ void sts64(uint32_t a, uint32_t v0, uint32_t v1) { asm volatile("st.shared.v2.b32 [%0], {%1,%2};" ::"r"(a), "r"(v0), "r"(v1) : "memory"); }
__device__ __forceinline__ void sts128(uint32_t a, uint32_t v0, uint32_t v1, uint32_t v2, uint32_t v3) { asm volatile("st.shared.v4.b32 [%0], {%1,%2,%3,%4};" ::"r"(a), "r"(v0), "r"(v1), "r"(v2), "r"(v3) : "memory"); }
__device__ __forceinline__ void lds64(uint32_t a, uint32_t& v0, uint32_t& v1) { asm volatile("ld.shared.v2.b32 {%0,%1}, [%2];" : "=r"(v0), "=r"(v1) : "r"(a) : "memory"); }
__device__ __forceinline__ void lds128(uint32_t a, uint32_t& v0, uint32_t& v1, uint32_t& v2, uint32_t& v3) { asm volatile("ld.shared.v4.b32 {%0,%1,%2,%3}, [%4];" : "=r"(v0), "=r"(v1), "=r"(v2), "=r"(v3) : "r"(a) : "memory"); }
__device__ __forceinline__ void ldsm4(uint32_t a, uint32_t& v0, uint32_t& v1, uint32_t& v2, uint32_t& v3) { asm volatile("ldmatrix.sync.aligned.m8n8.x4.shared.b16 {%0,%1,%2,%3}, [%4];" : "=r"(v0), "=r"(v1), "=r"(v2), "=r"(v3) : "r"(a) : "memory"); }
__device__ __forceinline__ void ldg128(const void* p, uint32_t& v0, uint32_t& v1, uint32_t& v2, uint32_t& v3) { asm volatile("ld.global.cg.v4.b32 {%0,%1,%2,%3}, [%4];" : "=r"(v0), "=r"(v1), "=r"(v2), "=r"(v3) : "l"(p) : "memory"); }
__device__ __forceinline__ void ldg64(const void* p, uint32_t& v0, uint32_t& v1) { asm volatile("ld.global.cg.v2.b32 {%0,%1}, [%2];" : "=r"(v0), "=r"(v1) : "l"(p) : "memory"); }
__device__ __forceinline__ uint32_t ldg32(const void* p) { uint32_t v; asm volatile("ld.global.b32 %0, [%1];" : "=r"(v) : "l"(p) : "memory"); return v; }
__device__ __forceinline__ void stg32(void* p, uint32_t v) { asm volatile("st.global.b32 [%0], %1;" ::"l"(p), "r"(v) : "memory"); }
__device__ __forceinline__ void signal(unsigned* c) { asm volatile("red.relaxed.gpu.global.add.u32 [%0], 1;" ::"l"(c) : "memory"); }
__device__ __forceinline__ void signal_release(unsigned* c) { asm volatile("red.release.gpu.global.add.u32 [%0], 1;" ::"l"(c) : "memory"); }
__device__ __forceinline__ void poll(const unsigned* c, unsigned target) {
  unsigned v; int n = 0;
  do { asm volatile("ld.relaxed.gpu.global.u32 %0, [%1];" : "=r"(v) : "l"(c) : "memory"); } while ((int)(v - target) < 0 && ++n < SPIN_LIMIT);
}

template <int INC, int SCALE_D>
__device__ __forceinline__ void wgmma_rs(float (&d)[16], uint32_t a0, uint32_t a1, uint32_t a2, uint32_t a3, uint64_t& bd) {
  asm volatile("{\n.reg .pred p;\nsetp.ne.b32 p, %22, 0;\n"
    "wgmma.mma_async.sync.aligned.m64n32k16.f32.bf16.bf16 {%0, %1, %2, %3, %4, %5, %6, %7, %8, %9, %10, %11, %12, %13, %14, %15}, {%17, %18, %19, %20}, %16, p, 1, 1, 1;\n"
    "add.s64 %16, %16, %21;\n}\n"
    : "+f"(d[0]), "+f"(d[1]), "+f"(d[2]), "+f"(d[3]), "+f"(d[4]), "+f"(d[5]), "+f"(d[6]), "+f"(d[7]), "+f"(d[8]), "+f"(d[9]), "+f"(d[10]), "+f"(d[11]), "+f"(d[12]), "+f"(d[13]), "+f"(d[14]), "+f"(d[15]), "+l"(bd)
    : "r"(a0), "r"(a1), "r"(a2), "r"(a3), "n"(INC), "n"(SCALE_D));
}
template <int INC, int SCALE_D>
__device__ __forceinline__ void wgmma_rs(float (&d)[20], uint32_t a0, uint32_t a1, uint32_t a2, uint32_t a3, uint64_t& bd) {
  asm volatile("{\n.reg .pred p;\nsetp.ne.b32 p, %26, 0;\n"
    "wgmma.mma_async.sync.aligned.m64n40k16.f32.bf16.bf16 {%0, %1, %2, %3, %4, %5, %6, %7, %8, %9, %10, %11, %12, %13, %14, %15, %16, %17, %18, %19}, {%21, %22, %23, %24}, %20, p, 1, 1, 1;\n"
    "add.s64 %20, %20, %25;\n}\n"
    : "+f"(d[0]), "+f"(d[1]), "+f"(d[2]), "+f"(d[3]), "+f"(d[4]), "+f"(d[5]), "+f"(d[6]), "+f"(d[7]), "+f"(d[8]), "+f"(d[9]), "+f"(d[10]), "+f"(d[11]), "+f"(d[12]), "+f"(d[13]), "+f"(d[14]), "+f"(d[15]), "+f"(d[16]), "+f"(d[17]), "+f"(d[18]), "+f"(d[19]), "+l"(bd)
    : "r"(a0), "r"(a1), "r"(a2), "r"(a3), "n"(INC), "n"(SCALE_D));
}
template <int INC, int SCALE_D>
__device__ __forceinline__ void wgmma_rs(float (&d)[32], uint32_t a0, uint32_t a1, uint32_t a2, uint32_t a3, uint64_t& bd) {
  asm volatile("{\n.reg .pred p;\nsetp.ne.b32 p, %38, 0;\n"
    "wgmma.mma_async.sync.aligned.m64n64k16.f32.bf16.bf16 {%0, %1, %2, %3, %4, %5, %6, %7, %8, %9, %10, %11, %12, %13, %14, %15, %16, %17, %18, %19, %20, %21, %22, %23, %24, %25, %26, %27, %28, %29, %30, %31}, {%33, %34, %35, %36}, %32, p, 1, 1, 1;\n"
    "add.s64 %32, %32, %37;\n}\n"
    : "+f"(d[0]), "+f"(d[1]), "+f"(d[2]), "+f"(d[3]), "+f"(d[4]), "+f"(d[5]), "+f"(d[6]), "+f"(d[7]), "+f"(d[8]), "+f"(d[9]), "+f"(d[10]), "+f"(d[11]), "+f"(d[12]), "+f"(d[13]), "+f"(d[14]), "+f"(d[15]), "+f"(d[16]), "+f"(d[17]), "+f"(d[18]), "+f"(d[19]), "+f"(d[20]), "+f"(d[21]), "+f"(d[22]), "+f"(d[23]), "+f"(d[24]), "+f"(d[25]), "+f"(d[26]), "+f"(d[27]), "+f"(d[28]), "+f"(d[29]), "+f"(d[30]), "+f"(d[31]), "+l"(bd)
    : "r"(a0), "r"(a1), "r"(a2), "r"(a3), "n"(INC), "n"(SCALE_D));
}
template <int INC, int SCALE_D>
__device__ __forceinline__ void wgmma_rs(float (&d)[36], uint32_t a0, uint32_t a1, uint32_t a2, uint32_t a3, uint64_t& bd) {
  asm volatile("{\n.reg .pred p;\nsetp.ne.b32 p, %42, 0;\n"
    "wgmma.mma_async.sync.aligned.m64n72k16.f32.bf16.bf16 {%0, %1, %2, %3, %4, %5, %6, %7, %8, %9, %10, %11, %12, %13, %14, %15, %16, %17, %18, %19, %20, %21, %22, %23, %24, %25, %26, %27, %28, %29, %30, %31, %32, %33, %34, %35}, {%37, %38, %39, %40}, %36, p, 1, 1, 1;\n"
    "add.s64 %36, %36, %41;\n}\n"
    : "+f"(d[0]), "+f"(d[1]), "+f"(d[2]), "+f"(d[3]), "+f"(d[4]), "+f"(d[5]), "+f"(d[6]), "+f"(d[7]), "+f"(d[8]), "+f"(d[9]), "+f"(d[10]), "+f"(d[11]), "+f"(d[12]), "+f"(d[13]), "+f"(d[14]), "+f"(d[15]), "+f"(d[16]), "+f"(d[17]), "+f"(d[18]), "+f"(d[19]), "+f"(d[20]), "+f"(d[21]), "+f"(d[22]), "+f"(d[23]), "+f"(d[24]), "+f"(d[25]), "+f"(d[26]), "+f"(d[27]), "+f"(d[28]), "+f"(d[29]), "+f"(d[30]), "+f"(d[31]), "+f"(d[32]), "+f"(d[33]), "+f"(d[34]), "+f"(d[35]), "+l"(bd)
    : "r"(a0), "r"(a1), "r"(a2), "r"(a3), "n"(INC), "n"(SCALE_D));
}
template <int INC, int SCALE_D>
__device__ __forceinline__ void wgmma_rs(float (&d)[44], uint32_t a0, uint32_t a1, uint32_t a2, uint32_t a3, uint64_t& bd) {
  asm volatile("{\n.reg .pred p;\nsetp.ne.b32 p, %50, 0;\n"
    "wgmma.mma_async.sync.aligned.m64n88k16.f32.bf16.bf16 {%0, %1, %2, %3, %4, %5, %6, %7, %8, %9, %10, %11, %12, %13, %14, %15, %16, %17, %18, %19, %20, %21, %22, %23, %24, %25, %26, %27, %28, %29, %30, %31, %32, %33, %34, %35, %36, %37, %38, %39, %40, %41, %42, %43}, {%45, %46, %47, %48}, %44, p, 1, 1, 1;\n"
    "add.s64 %44, %44, %49;\n}\n"
    : "+f"(d[0]), "+f"(d[1]), "+f"(d[2]), "+f"(d[3]), "+f"(d[4]), "+f"(d[5]), "+f"(d[6]), "+f"(d[7]), "+f"(d[8]), "+f"(d[9]), "+f"(d[10]), "+f"(d[11]), "+f"(d[12]), "+f"(d[13]), "+f"(d[14]), "+f"(d[15]), "+f"(d[16]), "+f"(d[17]), "+f"(d[18]), "+f"(d[19]), "+f"(d[20]), "+f"(d[21]), "+f"(d[22]), "+f"(d[23]), "+f"(d[24]), "+f"(d[25]), "+f"(d[26]), "+f"(d[27]), "+f"(d[28]), "+f"(d[29]), "+f"(d[30]), "+f"(d[31]), "+f"(d[32]), "+f"(d[33]), "+f"(d[34]), "+f"(d[35]), "+f"(d[36]), "+f"(d[37]), "+f"(d[38]), "+f"(d[39]), "+f"(d[40]), "+f"(d[41]), "+f"(d[42]), "+f"(d[43]), "+l"(bd)
    : "r"(a0), "r"(a1), "r"(a2), "r"(a3), "n"(INC), "n"(SCALE_D));
}
template <int INCA, int INCB, int SCALE_D>
__device__ __forceinline__ void wgmma_ss_tt(float (&d)[12], uint64_t& ad, uint64_t& bd) {
  asm volatile("{\n.reg .pred p;\nsetp.ne.b32 p, %16, 0;\n"
    "wgmma.mma_async.sync.aligned.m64n24k16.f32.bf16.bf16 {%0, %1, %2, %3, %4, %5, %6, %7, %8, %9, %10, %11}, %12, %13, p, 1, 1, 1, 1;\n"
    "add.s64 %12, %12, %14;\nadd.s64 %13, %13, %15;\n}\n"
    : "+f"(d[0]), "+f"(d[1]), "+f"(d[2]), "+f"(d[3]), "+f"(d[4]), "+f"(d[5]), "+f"(d[6]), "+f"(d[7]), "+f"(d[8]), "+f"(d[9]), "+f"(d[10]), "+f"(d[11]), "+l"(ad), "+l"(bd)
    : "n"(INCA), "n"(INCB), "n"(SCALE_D));
}

__host__ __device__ constexpr uint32_t desc_lo(uint32_t addr, uint32_t lbo) { return ((addr & 0x3FFFF) >> 4) | ((lbo >> 4) << 16); }
__host__ __device__ constexpr uint32_t desc_hi(uint32_t sbo, uint32_t swz) { return (sbo >> 4) | (swz << 30); }
__host__ __device__ constexpr uint64_t desc64(uint32_t addr, uint32_t lbo, uint32_t sbo, uint32_t swz) { return ((uint64_t)desc_hi(sbo, swz) << 32) | desc_lo(addr, lbo); }
template <uint32_t OFF> __device__ __forceinline__ uint64_t dadd(uint64_t base) {
  uint64_t d;
  asm volatile("add.s64 %0, %1, %2;" : "=l"(d) : "l"(base), "n"(OFF));
  return d;
}
template <int I, int N, class F> __device__ __forceinline__ void static_for(F f) {
  if constexpr (I < N) { f(std::integral_constant<int, I>{}); static_for<I + 1, N>(f); }
}

template <int KS, int K0, int ROWB, int NA>
__device__ __forceinline__ void stage_issue(float (&acc)[NA], const uint32_t (&a)[144], uint64_t d) {
  wg_fence();
  static_for<0, KS>([&](auto kk) {
    constexpr int k = K0 + kk.value;
    wgmma_rs<ROWB, k != 0>(acc, a[4 * k], a[4 * k + 1], a[4 * k + 2], a[4 * k + 3], d);
  });
  wg_commit();
}
template <int KS, int K0, int ROWB, int IT, int NA>
__device__ __forceinline__ void stage_c(float (&acc)[NA], const uint32_t (&a)[144], uint64_t base) {
  constexpr uint32_t slot = IT & (NSLOT - 1);
  mbar_wait(A_FULL + 8 * slot, (IT >> 3) & 1);
  stage_issue<KS, K0, ROWB>(acc, a, dadd<slot * (SLOT_BYTES / 16)>(base));
}
template <int IT> __device__ __forceinline__ void release_c(int lane) {
  if (lane == 0) mbar_arrive(A_EMPTY + 8 * (IT & (NSLOT - 1)));
}
template <int K0>
__device__ __forceinline__ void stage_r(float (&acc)[32], const uint32_t (&a)[144], uint32_t t8, uint64_t base) {
  const uint32_t s8 = t8 & 56;
  mbar_wait(A_FULL + s8, (t8 >> 6) & 1);
  stage_issue<6, K0, 128>(acc, a, base + s8 * (SLOT_BYTES / 128));
}
__device__ __forceinline__ void release_r(uint32_t t8, int lane) {
  if (lane == 0) mbar_arrive(A_EMPTY + (t8 & 56));
}

template <int HI, int NEG>
__device__ __forceinline__ void softmax18(const float (&p)[36], uint32_t (&w)[9]) {
  constexpr float L2E = NEG ? -1.4426950408889634f : 1.4426950408889634f;
  float m = p[2 * HI];
#pragma unroll
  for (int i = 1; i < 18; i++) { const float v = p[4 * (i >> 1) + 2 * HI + (i & 1)]; m = NEG ? fminf(m, v) : fmaxf(m, v); }
  m *= -L2E;
  float e[18], s = 0.f;
#pragma unroll
  for (int i = 0; i < 18; i++) { e[i] = ex2(fmaf(p[4 * (i >> 1) + 2 * HI + (i & 1)], L2E, m)); s += e[i]; }
  s = rcp(s);
#pragma unroll
  for (int t = 0; t < 9; t++) w[t] = pack2(e[2 * t] * s, e[2 * t + 1] * s);
}
template <int HI, int NEG>
__device__ __forceinline__ void phik_piece(const float (&p)[36], uint32_t rowaddr, int c, int t7) {
  uint32_t w[9];
  softmax18<HI, NEG>(p, w);
  rowaddr += HI * 1024;
  sts128(rowaddr + ((((2 * NEG + 2 * c) & 7) ^ t7) << 4), w[0], w[1], w[2], w[3]);
  sts128(rowaddr + ((((2 * NEG + 1 + 2 * c) & 7) ^ t7) << 4), w[4], w[5], w[6], w[7]);
  sts32(rowaddr + ((((4 + 2 * c) & 7) ^ t7) << 4) + 4 * NEG, w[8]);
}
template <int HI, int NEG>
__device__ __forceinline__ void phiq_piece(const float (&p)[36], uint32_t (&fq)[36]) {
  uint32_t w[9];
  softmax18<HI, NEG>(p, w);
#pragma unroll
  for (int t = 0; t < 8; t++) fq[2 * (8 * NEG + t) + HI] = w[t];
  fq[2 * (16 + NEG) + HI] = w[8];
}

__device__ __forceinline__ void phi_mma0(float (&p)[36], const float (&a32)[16], float rlo, float rhi, uint64_t d) {
  uint32_t f[8];
#pragma unroll
  for (int j = 0; j < 4; j++) { f[2 * j] = pack2(a32[4 * j] * rlo, a32[4 * j + 1] * rlo); f[2 * j + 1] = pack2(a32[4 * j + 2] * rhi, a32[4 * j + 3] * rhi); }
  wg_fence();
  static_for<0, 2>([&](auto s) { wgmma_rs<16, s.value != 0>(p, f[4 * s.value], f[4 * s.value + 1], f[4 * s.value + 2], f[4 * s.value + 3], d); });
  wg_commit();
}
__device__ __forceinline__ void phi_mma1(float (&p)[36], const float (&a40)[20], float rlo, float rhi, uint64_t d) {
  uint32_t f[12];
#pragma unroll
  for (int j = 0; j < 5; j++) { f[2 * j] = pack2(a40[4 * j] * rlo, a40[4 * j + 1] * rlo); f[2 * j + 1] = pack2(a40[4 * j + 2] * rhi, a40[4 * j + 3] * rhi); }
  f[10] = 0; f[11] = 0;
  d = dadd<32>(d);
  wg_fence();
  static_for<0, 3>([&](auto s) { wgmma_rs<16, 1>(p, f[4 * s.value], f[4 * s.value + 1], f[4 * s.value + 2], f[4 * s.value + 3], d); });
  wg_commit();
}

__device__ __forceinline__ void stage_piece(uint32_t st, int lane, int odd, const uint32_t (&f)[16], uint32_t s0, uint32_t s1) {
  const uint32_t pf = st + odd * 256 + lane * 16;
#pragma unroll
  for (int s = 0; s < 4; s++) sts128(pf + s * 512, f[4 * s], f[4 * s + 1], f[4 * s + 2], f[4 * s + 3]);
  sts64(st + (odd ? 0 : 2048) + lane * 8, s0, s1);
}
template <int C>
__device__ __forceinline__ void land_read(uint32_t (&a)[144], uint32_t base, int lane) {
  static_for<6 * C, 6 * C + 6>([&](auto s) {
    constexpr int k = s.value;
    constexpr uint32_t o = C * 12288 + (k - 6 * C) * 512;
    if constexpr (k % 9 == 4) { lds64(base + o + lane * 8, a[4 * k], a[4 * k + 1]); lds64(base + o + 256 + lane * 8, a[4 * k + 2], a[4 * k + 3]); }
    else lds128(base + o + lane * 16, a[4 * k], a[4 * k + 1], a[4 * k + 2], a[4 * k + 3]);
  });
}
__device__ __forceinline__ void tail_read(uint32_t (&a)[144], const uint4* blk, int lane) {
  static_for<30, 36>([&](auto s) {
    constexpr int k = s.value;
    if constexpr (k % 9 == 4) {
      const uint2* p = reinterpret_cast<const uint2*>(blk + k * 32) + lane;
      ldg64(p, a[4 * k], a[4 * k + 1]); ldg64(p + 32, a[4 * k + 2], a[4 * k + 3]);
    } else ldg128(blk + k * 32 + lane, a[4 * k], a[4 * k + 1], a[4 * k + 2], a[4 * k + 3]);
  });
}

__device__ __forceinline__ float gelu(float hy) {
  const float t = tanh_(hy * fmaf(hy * hy, 0.285419265090f, 1.595769121606f));
  return fmaf(hy, t, hy);
}
template <int K0, int Q>
__device__ __forceinline__ void stage_g(float (&acc)[32], const uint32_t (&a)[144], uint32_t t8, uint64_t base, bool on,
                                        const float (&y)[32], float rlo, float rhi, uint32_t b1addr, uint32_t dst) {
  const uint32_t s8 = t8 & 56;
  uint32_t b[4], o[4];
  if (on) lds128(b1addr + Q * 64, b[0], b[1], b[2], b[3]);
  mbar_wait(A_FULL + s8, (t8 >> 6) & 1);
  uint64_t d = base + s8 * (SLOT_BYTES / 128);
  wg_fence();
  static_for<0, 6>([&](auto kk) {
    constexpr int k = K0 + kk.value, e = kk.value - 1;
    wgmma_rs<128, 1>(acc, a[4 * k], a[4 * k + 1], a[4 * k + 2], a[4 * k + 3], d);
    if constexpr (e == 0 || e == 2) {
      if (on) {
        o[e] = pack2(gelu(fmaf(y[8 * Q + 2 * e], rlo, __uint_as_float(b[e]))), gelu(fmaf(y[8 * Q + 2 * e + 1], rlo, __uint_as_float(b[e + 1]))));
        o[e + 1] = pack2(gelu(fmaf(y[8 * Q + 2 * e + 2], rhi, __uint_as_float(b[e]))), gelu(fmaf(y[8 * Q + 2 * e + 3], rhi, __uint_as_float(b[e + 1]))));
        if constexpr (e == 2) sts128(dst + Q * 512, o[0], o[1], o[2], o[3]); else asm volatile("" : "+r"(o[0]), "+r"(o[1]));
      }
    }
  });
  wg_commit();
}
__device__ __forceinline__ void out_tile(const float (&acc)[32], const CUtensorMap* m, uint32_t st, int col, int row, int lane) {
  const uint32_t ra = st + ((lane & 7) + (lane & 8)) * 128;
  const int x7 = (lane & 7) ^ (lane >> 4);
#pragma unroll
  for (int q = 0; q < 4; q++)
    asm volatile("stmatrix.sync.aligned.m8n8.x4.shared.b16 [%0], {%1,%2,%3,%4};" ::"r"(ra + (((2 * q) ^ x7) << 4)),
                 "r"(pack2(acc[8 * q + 0], acc[8 * q + 1])), "r"(pack2(acc[8 * q + 2], acc[8 * q + 3])),
                 "r"(pack2(acc[8 * q + 4], acc[8 * q + 5])), "r"(pack2(acc[8 * q + 6], acc[8 * q + 7])) : "memory");
  fence_async_smem();
  __syncwarp();
  if (lane == 0) {
    asm volatile("cp.reduce.async.bulk.tensor.2d.global.shared::cta.add.tile.bulk_group [%0, {%2, %3}], [%1];" ::"l"(m), "r"(st), "r"(col), "r"(row) : "memory");
    bulk_commit();
    asm volatile("cp.async.bulk.wait_group.read 6;" ::: "memory");
  }
}

__global__ void __launch_bounds__(384, 1) fused_block_kernel(const __grid_constant__ Params P) {
  extern __shared__ __align__(1024) uint8_t smem_raw[];
  if ((uint32_t)__cvta_generic_to_shared(smem_raw) != SB) return;
  const int tid = threadIdx.x, warp = __shfl_sync(0xffffffffu, tid >> 5, 0), lane = __shfl_sync(0xffffffffu, tid & 31, tid & 31);
  const int blk = blockIdx.x;
  int r, g;
  {
    const int q = blk >> 3, u = q >> 1;
    const int R = (u < 4) ? u : 7 - u;
    const int G = ((u >> 2) << 1) | ((q ^ u) & 1);
    r = 4 * R + ((blk & 7) >> 1);
    g = 2 * G + (blk & 1);
  }
  const int odd = g & 1;

  if (warp >= 8) {
    asm volatile("setmaxnreg.dec.sync.aligned.u32 24;");
    if (warp == 8) {
      if (lane == 0) {
#pragma unroll
        for (int s = 0; s < NSLOT; s++) { mbar_init(A_FULL + 8 * s, 1); mbar_init(A_EMPTY + 8 * s, 8); }
        mbar_init(A_XFREE, 8); mbar_init(A_KVL, 1); mbar_init(A_OUTRDY, 1);
        fence_async_smem();
      }
      __syncwarp();
      bar_arrive<BAR_INIT, 384>();
      if (lane == 0) {
        const int c64 = 72 * g + (odd ? -8 : 32), c32 = 72 * g + (odd ? 40 : 0);
#pragma unroll 1
        for (uint32_t it = 0; it < 144; it++) {
          const CUtensorMap* m; int c0, c1;
          if (it < 27) {
            const int sec = it / 9, s = it - 9 * sec, s32 = (sec == 1) ? s - 6 : s, s64 = (sec == 1) ? s : s - 3;
            const bool n32 = (unsigned)s32 < 3u;
            m = n32 ? &P.tq32 : &P.tq64;
            c0 = (sec == 2 ? 0 : (sec + 1) * D_) + (n32 ? c32 : c64);
            c1 = n32 ? 192 * s32 : 96 * s64;
          } else if (it < 36) {
            const int t = (it - 27) / 3, s = it - 27 - 3 * t;
            m = s == 2 ? &P.to32 : &P.to64;
            c0 = s == 2 ? c32 : c64;
            c1 = 192 * t + (s == 1 ? 96 : 0);
          } else {
            const int p = (it - 36) / 6, s = it - 36 - 6 * p;
            m = p < 9 ? &P.tw1 : &P.tw2;
            c0 = p < 9 ? D_ * g + 64 * p : 64 * (p - 9);
            c1 = p < 9 ? 96 * s : D_ * g + 96 * s;
          }
          const uint32_t slot = it & (NSLOT - 1);
          if (it == 6) mbar_wait(A_XFREE, 0);
          mbar_wait(A_EMPTY + 8 * slot, ((it >> 3) & 1) ^ 1);
          mbar_expect_tx(A_FULL + 8 * slot, SLOT_BYTES);
          tma2d(SB + slot * SLOT_BYTES, m, c0, c1, A_FULL + 8 * slot);
        }
      }
    } else {
      const int ht = tid - 288, hw = warp - 9;
      const bool feeder = (hw < 2) && lane == 0;
      const uint32_t lb = A_LAND + hw * 40, H = A_X + hw * 65536;
      if (feeder) {
#pragma unroll
        for (int i = 0; i < 5; i++) mbar_init(lb + 8 * i, 1);
        fence_async_smem();
#pragma unroll
        for (int i = 0; i < 3; i++) { mbar_expect_tx(lb + 8 * i, 24576); tma3d(A_XT + hw * 73728 + i * 24576, &P.tx, r * 128 + hw * 64, 3 * i, lb + 8 * i); }
        mbar_arrive(lb + 24); mbar_arrive(lb + 32);
      }
      if (ht == 64) l2_prefetch(reinterpret_cast<const char*>(P.wqkv) + blk * 15552, 15552);
      const unsigned ep1 = ldg32(&g_epoch[blk]) + 1;
      uint32_t wv[7], bv[3];
      {
        const uint32_t* wp = reinterpret_cast<const uint32_t*>(P.wphi) + g * 648 + ht;
#pragma unroll
        for (int i = 0; i < 7; i++) if (i < 6 || ht < 72) wv[i] = ldg32(wp + 96 * i);
        const uint32_t* bp = reinterpret_cast<const uint32_t*>(P.b1) + g * 288 + ht;
#pragma unroll
        for (int i = 0; i < 3; i++) bv[i] = ldg32(bp + 96 * i);
      }
      bar_sync<BAR_INIT, 384>();
#pragma unroll
      for (int i = 0; i < 3; i++)
        sts64(A_B1 + (ht >> 3) * 64 + (ht & 3) * 16 + (ht & 4) * 2 + i * 768, __float_as_uint(0.5f * bf_lo(bv[i])), __float_as_uint(0.5f * bf_hi(bv[i])));
      if (ht < 45) g_kv[((ep1 & 1) * 8 + g) * 720 + r * 45 + ht] = make_float4(0.f, 0.f, 0.f, 0.f);
      mbar_wait(A_XFREE, 0);
      if (ht == 64) l2_prefetch(reinterpret_cast<const char*>(P.wo) + blk * 5184, 5184);
      if (ht == 65) l2_prefetch(reinterpret_cast<const char*>(P.w1) + blk * 41472, 41472);
      if (ht == 66) l2_prefetch(reinterpret_cast<const char*>(P.w2) + blk * 41472, 41472);
#pragma unroll 1
      for (int i = ht; i < 720; i += 96) sts128(A_WPHI + i * 16, 0, 0, 0, 0);
      bar_sync<BAR_HELP, 96>();
      {
        const int c40 = odd ? 0 : 32, c32 = odd ? 40 : 0;
#pragma unroll
        for (int i = 0; i < 7; i++) {
          const int e = ht + 96 * i, col = e / 9, t = e - col * 9, h = col / 18;
          const int kk = (col >= c40 && col < c40 + 40) ? 32 + col - c40 : col - c32;
          if (i < 6 || ht < 72) sts32(A_WPHI + t * 1280 + kk * 16 + 4 * h, wv[i]);
        }
      }
#pragma unroll 1
      for (int i = ht; i < 512; i += 96) sts128(A_V + (i >> 7) * 6144 + 4096 + (i & 127) * 16, 0, 0x00003f80u, 0, 0);
      fence_async_smem();
      bar_arrive<BAR_PREP, 352>();
#pragma unroll 1
      for (int i = ht; i < 1584; i += 96) sts128(A_KVB + i * 16, 0, 0, 0, 0);
      if (hw == 0) {
        bar_sync<BAR_KVOUT, 288>();
        if (lane == 0) {
          TSX(288, 20);
          float4* kv = g_kv + (((ep1 + 1) & 1) * 8 + g) * 720;
#pragma unroll
          for (int h = 0; h < 4; h++)
            asm volatile("cp.reduce.async.bulk.global.shared::cta.bulk_group.add.f32 [%0], [%1], %2;" ::"l"(kv + h * 180), "r"(A_V + h * 6144), "r"(2880) : "memory");
          bulk_commit();
          mbar_expect_tx(A_KVL, 11520);
          bulk_wait_all();
          signal(&g_cnt[g * 32]);
          TSX(288, 21);
          poll(&g_cnt[g * 32], ep1 * 16);
          TSX(288, 22);
          bulk_load(A_PHI, kv, 11520, A_KVL);
        }
      }
      const int f0 = ht / 5, kq = ht - 5 * f0, f1 = f0 + 18;
      const uint32_t kr0 = A_KVB + (16 * (f0 >> 2) + 8 * ((f0 >> 1) & 1) + (f0 & 1)) * 16, kr1 = A_KVB + (16 * (f1 >> 2) + 8 * ((f1 >> 1) & 1) + (f1 & 1)) * 16;
      bar_sync<BAR_HELP, 96>();
      mbar_wait(A_KVL, 0);
      TSX(288, 23);
      if (ht < 90) {
#pragma unroll
        for (int h = 0; h < 4; h++) {
          const int n0 = 18 * h + 4 * kq, n1 = n0 + 2;
          const uint32_t c0 = (n0 >> 3) * 2304 + (n0 & 7) * 2 + 32 * h, c1 = (n1 >> 3) * 2304 + (n1 & 7) * 2 + 32 * h;
#pragma unroll
          for (int u = 0; u < 2; u++) {
            uint32_t v0, v1, v2, v3;
            lds128(A_PHI + ht * 16 + h * 2880 + u * 1440, v0, v1, v2, v3);
            const uint32_t ra = u ? kr1 : kr0;
            sts32(ra + c0, pack2(__uint_as_float(v0), __uint_as_float(v1)));
            if (kq < 4) sts32(ra + c1, pack2(__uint_as_float(v2), __uint_as_float(v3)));
            else {
              const uint32_t zz = (h & 1) ? pack2(0.f, __uint_as_float(v2)) : pack2(__uint_as_float(v2), 0.f);
              sts128(ra + 32 * h + (9 + (h >> 1)) * 2304, zz, zz, zz, zz);
            }
          }
        }
      }
      fence_async_smem();
      bar_arrive<BAR_KVB, 352>();
      TSX(288, 24);
      if (hw < 2) {
        bar_sync<BAR_OMMA, 320>();
        if (lane == 0) {
#pragma unroll 1
          for (int x = 0; x < 2; x++) {
            poll(&g_cnt[(8 + 32 * x + 2 * r + hw) * 32], ep1 * 32);
            TSX(288, 25 + x);
            mbar_expect_tx(lb, x ? 16384 : 12288);
            if (x) bulk_load(H + 61440, g_stats + (r * 8 + hw * 4) * 64, 4096, lb);
#pragma unroll 1
            for (int i = 0; i < 5; i++) {
              if (i) mbar_expect_tx(lb + 8 * i, 12288);
              tma3d(H + i * 12288, x ? &P.tgh : &P.tgo, 3 * i, r * 8 + hw * 4, lb + 8 * i);
            }
          }
          mbar_wait(lb + 32, 0);
        }
      }
      bar_sync<BAR_HELP, 96>();
#pragma unroll 1
      for (int u = hw; u < 18; u += 3) {
        const int j = u >> 1, w0 = r * 8 + (u & 1) * 4, J = 9 * g + j;
        const bool split = (j == (odd ? 0 : 8));
        const uint2* src = reinterpret_cast<const uint2*>(g_h + (w0 * 36 + (J >> 1)) * 32) + (split ? (J & 1) * 32 + lane : (J & 1) + 2 * lane);
        const int col = 8 * J + 2 * (lane & 3);
        const uint32_t b = ldg32(P.b2 + col);
        uint32_t v[8];
#pragma unroll
        for (int w = 0; w < 4; w++) ldg64(src + w * 2304, v[2 * w], v[2 * w + 1]);
        __nv_bfloat16* o = P.out + (size_t)(w0 * 16 + (lane >> 2)) * D_ + col;
#pragma unroll
        for (int w = 0; w < 8; w++) stg32(o + w * 8 * D_, hadd2(v[w], b));
      }
      bar_sync<BAR_HELP, 96>();
      if (ht == 0) {
        signal_release(&g_cnt[(72 + r) * 32]);
        poll(&g_cnt[(72 + r) * 32], ep1 * 8);
        asm volatile("fence.acq_rel.gpu;" ::: "memory");
        mbar_arrive(A_OUTRDY);
        g_epoch[blk] = ep1;
        TSX(288, 27);
      }
    }
  } else {
    asm volatile("setmaxnreg.inc.sync.aligned.u32 240;");
    TS(0);
    TSG(30);
    const int c = lane & 3, rq = lane >> 2, wg = warp >> 2, wq = warp & 3;
    const uint64_t z = P.d64, o40 = P.d128 + odd;
    const uint32_t lb = A_LAND + wg * 40;
    uint32_t a[144];
    float rlo, rhi;
    bar_sync<BAR_INIT, 384>();
    {
      const uint32_t xr = A_XT + wg * 73728 + (wq * 16 + (lane & 15)) * 128;
      const int x7 = (lane & 7) ^ (lane >> 4);
      float sm[4] = {}, dl[2][4] = {}, dh[2][4] = {};
      static_for<0, 36>([&](auto s) {
        constexpr int k = s.value;
        if constexpr (k % 12 == 0) {
          mbar_wait(lb + 8 * (k / 12), 0);
          static_for<k, k + 12>([&](auto t) {
            constexpr int u = t.value;
            ldsm4(xr + (u >> 2) * 8192 + (((2 * (u & 3)) ^ x7) << 4), a[4 * u], a[4 * u + 1], a[4 * u + 2], a[4 * u + 3]);
          });
        }
        mma16816(sm, a[4 * k], a[4 * k + 1], a[4 * k + 2], a[4 * k + 3], 0x3f803f80u, 0x3f803f80u);
        mma1688(dl[0], a[4 * k], a[4 * k + 1], a[4 * k]);
        mma1688(dh[0], a[4 * k], a[4 * k + 1], a[4 * k + 1]);
        mma1688(dl[1], a[4 * k + 2], a[4 * k + 3], a[4 * k + 2]);
        mma1688(dh[1], a[4 * k + 2], a[4 * k + 3], a[4 * k + 3]);
      });
      const float mlo = sm[0] * (1.f / D_), mhi = sm[2] * (1.f / D_);
      if (lane == 0) asm volatile("mbarrier.arrive.shared::cta.b64 _, [%0];" ::"r"(A_XFREE), "f"(mlo) : "memory");
      float ql = (rq & 1) ? dl[0][1] + dl[1][1] : dl[0][0] + dl[1][0];
      float qh = (rq & 1) ? dh[0][3] + dh[1][3] : dh[0][2] + dh[1][2];
      ql = __shfl_sync(0xffffffffu, ql, (lane & 28) | (rq >> 1));
      qh = __shfl_sync(0xffffffffu, qh, (lane & 28) | (rq >> 1));
      rlo = rsq(fmaxf(ql * (1.f / D_) - mlo * mlo, 0.f) + 1e-5f);
      rhi = rsq(fmaxf(qh * (1.f / D_) - mhi * mhi, 0.f) + 1e-5f);
      const uint32_t ml = pack2(mlo, mlo), mh = pack2(mhi, mhi);
#pragma unroll
      for (int i = 0; i < 144; i++) a[i] = hsub2(a[i], (i & 1) ? mh : ml);
    }
    TS(1);
    uint32_t fq[36];
    {
      float k40[20], k32[16], v40[20], v32[16], p[36];
      stage_c<12, 0, 64, 0>(k32, a, z);
      stage_c<12, 12, 64, 1>(k32, a, z);    wg_wait<1>(); release_c<0>(lane);
      stage_c<12, 24, 64, 2>(k32, a, z);    wg_wait<1>(); release_c<1>(lane);
      stage_c<6, 0, 128, 3>(k40, a, o40);   wg_wait<1>(); pin(k32); release_c<2>(lane);
      stage_c<6, 6, 128, 4>(k40, a, o40);   wg_wait<1>(); release_c<3>(lane);
      stage_c<6, 12, 128, 5>(k40, a, o40);  wg_wait<1>(); release_c<4>(lane);
      stage_c<6, 18, 128, 6>(k40, a, o40);
      bar_sync<BAR_PREP, 352>();
      phi_mma0(p, k32, rlo, rhi, P.dwphi);        wg_wait<1>(); release_c<5>(lane); release_c<6>(lane);
      stage_c<6, 24, 128, 7>(k40, a, o40);
      stage_c<6, 30, 128, 8>(k40, a, o40);  wg_wait<1>(); release_c<7>(lane);
      wg_wait<0>(); pin(k40); release_c<8>(lane);
      TS(2);
      phi_mma1(p, k40, rlo, rhi, P.dwphi);
      stage_c<6, 0, 128, 9>(v40, a, o40);   wg_wait<1>(); pin(p);
      const uint32_t prow = A_PHI + c * 16384 + (warp * 16 + rq) * 128;
      stage_c<6, 6, 128, 10>(v40, a, o40);
      stage_c<6, 12, 128, 11>(v40, a, o40); phik_piece<0, 0>(p, prow, c, rq); wg_wait<1>(); release_c<9>(lane); release_c<10>(lane);
      stage_c<6, 18, 128, 12>(v40, a, o40); phik_piece<0, 1>(p, prow, c, rq); wg_wait<1>(); release_c<11>(lane);
      stage_c<6, 24, 128, 13>(v40, a, o40); phik_piece<1, 0>(p, prow, c, rq); wg_wait<1>(); release_c<12>(lane);
      stage_c<6, 30, 128, 14>(v40, a, o40); phik_piece<1, 1>(p, prow, c, rq); wg_wait<1>(); release_c<13>(lane);
      stage_c<12, 0, 64, 15>(v32, a, z);    wg_wait<1>(); release_c<14>(lane);
      stage_c<12, 12, 64, 16>(v32, a, z);   wg_wait<1>(); release_c<15>(lane);
      stage_c<12, 24, 64, 17>(v32, a, z);   wg_wait<1>(); release_c<16>(lane);
      TS(3);
      stage_c<12, 0, 64, 18>(k32, a, z);    wg_wait<1>(); pin(v40); pin(v32); release_c<17>(lane);
      {
        const int c40 = odd ? 0 : 32, c32 = odd ? 40 : 0;
        const uint32_t vrow = A_V + (warp * 16 + rq) * 16;
#pragma unroll
        for (int j = 0; j < 9; j++) {
          const int col = (j < 5 ? c40 + 8 * j : c32 + 8 * (j - 5)) + 2 * c;
          const int h = (col * 57) >> 10, d = col - 18 * h;
          const uint32_t ad = vrow + h * 6144 + (d >> 3) * 2048 + (d & 7) * 2;
          const float* v = j < 5 ? &v40[4 * j] : &v32[4 * (j - 5)];
          sts32(ad, pack2(v[0] * rlo, v[1] * rlo));
          sts32(ad + 128, pack2(v[2] * rhi, v[3] * rhi));
        }
      }
      fence_async_smem();
      bar_sync<BAR_KVIN, 256>();
      float kv0[12], kv1[12];
      {
        uint64_t da = P.dphi + wg * 2048, db = P.dv + wg * 768;
        wg_fence();
        static_for<0, 8>([&](auto s) { wgmma_ss_tt<128, s.value == 7 ? 384 - 112 : 16, s.value != 0>(kv0, da, db); });
        static_for<0, 8>([&](auto s) { wgmma_ss_tt<128, 16, s.value != 0>(kv1, da, db); });
        wg_commit();
      }
      stage_c<12, 12, 64, 19>(k32, a, z);   wg_wait<1>(); pin(kv0); pin(kv1); release_c<18>(lane);
      bar_sync_wg(wg);
#pragma unroll
      for (int hh = 0; hh < 2; hh++) {
#pragma unroll
        for (int u = 0; u < 2; u++) {
          const int f = 8 * ((2 * wq + u - 4 * wg - 2 * hh) & 7) + rq;
          if (f < 36) {
            const uint32_t ad = A_V + (2 * wg + hh) * 6144 + f * 80 + c * 8;
            const float* kvp = hh ? kv1 : kv0;
            sts64(ad, __float_as_uint(kvp[2 * u]), __float_as_uint(kvp[2 * u + 1]));
            sts64(ad + 32, __float_as_uint(kvp[4 + 2 * u]), __float_as_uint(kvp[5 + 2 * u]));
            if (c < 2) sts64(ad + 64, __float_as_uint(kvp[8 + 2 * u]), __float_as_uint(kvp[9 + 2 * u]));
          }
        }
      }
      fence_async_smem();
      bar_arrive<BAR_KVOUT, 288>();
      stage_c<12, 24, 64, 20>(k32, a, z);   wg_wait<1>(); release_c<19>(lane);
      stage_c<6, 0, 128, 21>(k40, a, o40);  wg_wait<1>(); pin(k32); release_c<20>(lane);
      stage_c<6, 6, 128, 22>(k40, a, o40);
      phi_mma0(p, k32, rlo, rhi, P.dwphi);        wg_wait<1>(); release_c<21>(lane); release_c<22>(lane);
      stage_c<6, 12, 128, 23>(k40, a, o40);
      stage_c<6, 18, 128, 24>(k40, a, o40); wg_wait<1>(); release_c<23>(lane);
      stage_c<6, 24, 128, 25>(k40, a, o40); wg_wait<1>(); release_c<24>(lane);
      stage_c<6, 30, 128, 26>(k40, a, o40); wg_wait<1>(); release_c<25>(lane);
      wg_wait<0>(); pin(k40); release_c<26>(lane);
      TS(4);
      phi_mma1(p, k40, rlo, rhi, P.dwphi);
      wg_wait<0>(); pin(p);
      phiq_piece<0, 0>(p, fq); phiq_piece<1, 0>(p, fq); phiq_piece<0, 1>(p, fq); phiq_piece<1, 1>(p, fq);
    }
    TS(5);
    uint32_t xr[18];
    {
      const __nv_bfloat16* xp = P.x + (size_t)(r * 128 + warp * 16 + rq) * D_ + 72 * g + 2 * c;
      const __nv_bfloat16 *x40 = xp + (odd ? 0 : 32), *x32 = xp + (odd ? 40 : 0);
#pragma unroll
      for (int j = 0; j < 9; j++) {
        const __nv_bfloat16* q = j < 5 ? x40 + 8 * j : x32 + 8 * (j - 5);
        xr[2 * j] = ldg32(q);
        xr[2 * j + 1] = ldg32(q + 8 * D_);
      }
    }
    const int rw = r * 8 + warp;
    const uint32_t land = A_X + wg * 65536 + wq * 3072;
    {
      float o[44];
      uint64_t d = P.dkvb;
      bar_sync<BAR_KVB, 352>();
      TS(6);
      wg_fence();
      static_for<0, 9>([&](auto s) { wgmma_rs<16, s.value != 0>(o, fq[4 * s.value], fq[4 * s.value + 1], fq[4 * s.value + 2], fq[4 * s.value + 3], d); });
      wg_commit();
      wg_wait<0>(); pin(o);
      bar_arrive<BAR_OMMA, 320>();
      uint32_t f[18], ff[16];
#pragma unroll
      for (int u = 0; u < 2; u++) {
        const float i0 = rcp(o[36 + 2 * u] + 1e-6f), i1 = rcp(o[37 + 2 * u] + 1e-6f), i2 = rcp(o[40 + 2 * u] + 1e-6f), i3 = rcp(o[41 + 2 * u] + 1e-6f);
        const float sc[9] = {i0, i0, c < 1 ? i0 : i1, i1, c < 2 ? i1 : i2, i2, c < 3 ? i2 : i3, i3, i3};
#pragma unroll
        for (int j = 0; j < 9; j++) f[2 * j + u] = pack2(o[4 * j + 2 * u] * sc[j], o[4 * j + 2 * u + 1] * sc[j]);
      }
#pragma unroll
      for (int i = 0; i < 16; i++) ff[i] = odd ? f[i + 2] : f[i];
      stage_piece(land, lane, odd, ff, odd ? f[0] : f[16], odd ? f[1] : f[17]);
      fence_async_smem();
      __syncwarp();
      if (lane == 0) {
        bulk_store(reinterpret_cast<char*>(g_o + rw * 1152) + g * 2304, land, 2304);
        bulk_commit(); bulk_wait_all();
        signal(&g_cnt[(8 + 2 * r + wg) * 32]);
      }
      TS(7);
    }
    {
      float h40[20], h32[16];
      mbar_wait(lb, 1);
      TS(8);
      tail_read(a, g_o + rw * 1152, lane);
      land_read<0>(a, land, lane);                          stage_c<6, 0, 128, 27>(h40, a, o40);
      mbar_wait(lb + 8, 1);  land_read<1>(a, land, lane);   stage_c<6, 6, 128, 28>(h40, a, o40);  wg_wait<1>(); release_c<27>(lane);
      stage_c<12, 0, 64, 29>(h32, a, z);
      mbar_wait(lb + 16, 1); land_read<2>(a, land, lane);   wg_wait<1>(); release_c<28>(lane);
      stage_c<6, 12, 128, 30>(h40, a, o40);
      mbar_wait(lb + 24, 1); land_read<3>(a, land, lane);   wg_wait<1>(); release_c<29>(lane);
      stage_c<6, 18, 128, 31>(h40, a, o40); wg_wait<1>(); release_c<30>(lane);
      stage_c<12, 12, 64, 32>(h32, a, z);
      mbar_wait(lb + 32, 1); land_read<4>(a, land, lane);   wg_wait<1>(); release_c<31>(lane);
      stage_c<6, 24, 128, 33>(h40, a, o40); wg_wait<1>(); release_c<32>(lane);
      stage_c<6, 30, 128, 34>(h40, a, o40); wg_wait<1>(); release_c<33>(lane);
      stage_c<12, 24, 64, 35>(h32, a, z);   wg_wait<1>(); release_c<34>(lane);
      wg_wait<0>(); pin(h40); pin(h32); release_c<35>(lane);
      TS(9);
      uint32_t f[18], ff[16];
      float sl = 0.f, ql = 0.f, sh = 0.f, qh = 0.f;
#pragma unroll
      for (int j = 0; j < 9; j++) {
        const float* v = j < 5 ? &h40[4 * j] : &h32[4 * (j - 5)];
        f[2 * j] = pack2(v[0] + bf_lo(xr[2 * j]), v[1] + bf_hi(xr[2 * j]));
        f[2 * j + 1] = pack2(v[2] + bf_lo(xr[2 * j + 1]), v[3] + bf_hi(xr[2 * j + 1]));
      }
#pragma unroll
      for (int i = 0; i < 8; i++) { ff[i] = odd ? f[i + 2] : f[i + 10]; ff[8 + i] = odd ? f[i + 10] : f[i]; }
      stage_piece(land, lane, odd, ff, odd ? f[0] : f[8], odd ? f[1] : f[9]);
#pragma unroll
      for (int j = 0; j < 9; j++) {
        const float l0 = bf_lo(f[2 * j]), l1 = bf_hi(f[2 * j]), u0 = bf_lo(f[2 * j + 1]), u1 = bf_hi(f[2 * j + 1]);
        sl += l0 + l1; ql = fmaf(l0, l0, fmaf(l1, l1, ql));
        sh += u0 + u1; qh = fmaf(u0, u0, fmaf(u1, u1, qh));
      }
#pragma unroll
      for (int m = 1; m < 4; m <<= 1) {
        sl += __shfl_xor_sync(0xffffffffu, sl, m); ql += __shfl_xor_sync(0xffffffffu, ql, m);
        sh += __shfl_xor_sync(0xffffffffu, sh, m); qh += __shfl_xor_sync(0xffffffffu, qh, m);
      }
      if (c == 0) sts128(land + 2304 + rq * 16, __float_as_uint(sl), __float_as_uint(ql), __float_as_uint(sh), __float_as_uint(qh));
      fence_async_smem();
      __syncwarp();
      if (lane == 0) {
        bulk_store(reinterpret_cast<char*>(g_h + rw * 1152) + g * 2304, land, 2304);
        bulk_store(g_stats + rw * 64 + g * 8, land + 2304, 128);
        bulk_commit(); bulk_wait_all();
        signal(&g_cnt[(40 + 2 * r + wg) * 32]);
      }
      TS(10);
    }
    float accA[32], accB[32];
    {
      mbar_wait(lb, 0);
      TS(11);
      tail_read(a, g_h + rw * 1152, lane);
      uint32_t s0, s1, s2, s3, t0, t1, t2, t3;
      const uint32_t sa = A_X + wg * 65536 + 61440 + wq * 1024 + c * 256 + rq * 16;
      lds128(sa, s0, s1, s2, s3);
      lds128(sa + 128, t0, t1, t2, t3);
      land_read<0>(a, land, lane);
      float sl = __uint_as_float(s0) + __uint_as_float(t0), ql = __uint_as_float(s1) + __uint_as_float(t1);
      float sh = __uint_as_float(s2) + __uint_as_float(t2), qh = __uint_as_float(s3) + __uint_as_float(t3);
#pragma unroll
      for (int m = 1; m < 4; m <<= 1) {
        sl += __shfl_xor_sync(0xffffffffu, sl, m); ql += __shfl_xor_sync(0xffffffffu, ql, m);
        sh += __shfl_xor_sync(0xffffffffu, sh, m); qh += __shfl_xor_sync(0xffffffffu, qh, m);
      }
      sl *= (1.f / D_); sh *= (1.f / D_);
      rlo = 0.5f * rsq(fmaxf(ql * (1.f / D_) - sl * sl, 0.f) + 1e-5f);
      rhi = 0.5f * rsq(fmaxf(qh * (1.f / D_) - sh * sh, 0.f) + 1e-5f);
      const uint32_t ml = pack2(sl, sl), mh = pack2(sh, sh);
      auto center = [&](int k0) {
#pragma unroll
        for (int i = 4 * k0; i < 4 * k0 + 24; i++) a[i] = hsub2(a[i], (i & 1) ? mh : ml);
      };
      center(0);                                                       stage_c<6, 0, 128, 36>(accA, a, P.d128);
      mbar_wait(lb + 8, 0);  land_read<1>(a, land, lane); center(6);   stage_c<6, 6, 128, 37>(accA, a, P.d128);
      mbar_wait(lb + 16, 0); land_read<2>(a, land, lane); center(12);  wg_wait<1>(); release_c<36>(lane); stage_c<6, 12, 128, 38>(accA, a, P.d128);
      mbar_wait(lb + 24, 0); land_read<3>(a, land, lane); center(18);  wg_wait<1>(); release_c<37>(lane); stage_c<6, 18, 128, 39>(accA, a, P.d128);
      mbar_wait(lb + 32, 0); land_read<4>(a, land, lane); center(24);  wg_wait<1>(); release_c<38>(lane); stage_c<6, 24, 128, 40>(accA, a, P.d128);
      center(30);
      bar_sync_wg(wg);
      wg_wait<1>(); release_c<39>(lane);
    }
    TS(12);
    {
      const uint32_t xw = A_X + warp * 16384;
      const int grow = r * 128 + warp * 16;
      uint32_t t8 = 41 * 8;
#pragma unroll 1
      for (int i = 0; i < 9; i++) {
        const uint32_t b1a = A_B1 + c * 16 + i * 512, hd = xw + (i & 3) * 4096;
        stage_r<30>(accA, a, t8, P.d128); wg_wait<1>(); release_r(t8 - 8, lane);
        if (i == 4) {
          TS(13);
          wg_wait<0>();
#pragma unroll
          for (int s = 0; s < 32; s++) lds128(xw + lane * 16 + s * 512, a[4 * s], a[4 * s + 1], a[4 * s + 2], a[4 * s + 3]);
          mbar_wait(A_OUTRDY, 0);
          fence_async_global();
        }
        stage_r<0>(accB, a, t8 + 8, P.d128);   wg_wait<1>(); pin(accA); release_r(t8, lane);
        stage_g<6, 0>(accB, a, t8 + 16, P.d128, i <= 4, accA, rlo, rhi, b1a, hd + lane * 16);
        if (i > 4) out_tile(accA, &P.tout, hd, 128 * i - 576, grow, lane);
        wg_wait<1>(); release_r(t8 + 8, lane);
        stage_g<12, 1>(accB, a, t8 + 24, P.d128, i <= 4, accA, rlo, rhi, b1a, hd + lane * 16);
        wg_wait<1>(); release_r(t8 + 16, lane);
        stage_g<18, 2>(accB, a, t8 + 32, P.d128, i <= 4, accA, rlo, rhi, b1a, hd + lane * 16);
        wg_wait<1>(); release_r(t8 + 24, lane);
        stage_g<24, 3>(accB, a, t8 + 40, P.d128, i <= 4, accA, rlo, rhi, b1a, hd + lane * 16);
        if (i == 4) {
#pragma unroll
          for (int s = 0; s < 4; s++) lds128(xw + lane * 16 + s * 512, a[128 + 4 * s], a[129 + 4 * s], a[130 + 4 * s], a[131 + 4 * s]);
          TS(14);
        }
        wg_wait<1>(); release_r(t8 + 32, lane);
        stage_r<30>(accB, a, t8 + 48, P.d128); wg_wait<1>(); release_r(t8 + 40, lane);
        if (i < 8) { stage_r<0>(accA, a, t8 + 56, P.d128); wg_wait<1>(); } else { wg_wait<0>(); TS(15); }
        pin(accB); release_r(t8 + 48, lane);
        if (i < 8) stage_g<6, 0>(accA, a, t8 + 64, P.d128, i <= 3, accB, rlo, rhi, b1a + 256, hd + 2048 + lane * 16);
        if (i > 3) out_tile(accB, &P.tout, hd + 2048, 128 * i - 512, grow, lane);
        if (i < 8) {
          wg_wait<1>(); release_r(t8 + 56, lane);
          stage_g<12, 1>(accA, a, t8 + 72, P.d128, i <= 3, accB, rlo, rhi, b1a + 256, hd + 2048 + lane * 16);
          wg_wait<1>(); release_r(t8 + 64, lane);
          stage_g<18, 2>(accA, a, t8 + 80, P.d128, i <= 3, accB, rlo, rhi, b1a + 256, hd + 2048 + lane * 16);
          wg_wait<1>(); release_r(t8 + 72, lane);
          stage_g<24, 3>(accA, a, t8 + 88, P.d128, i <= 3, accB, rlo, rhi, b1a + 256, hd + 2048 + lane * 16);
          wg_wait<1>(); release_r(t8 + 80, lane);
        }
        t8 += 96;
      }
      wg_wait<0>();
      if (lane == 0) bulk_wait_all();
      TS(16);
      TSG(31);
      TS_DUMP();
    }
  }
}

typedef CUresult (*EncodeFn)(CUtensorMap*, CUtensorMapDataType, cuuint32_t, void*, const cuuint64_t*, const cuuint64_t*, const cuuint32_t*,
                             const cuuint32_t*, CUtensorMapInterleave, CUtensorMapSwizzle, CUtensorMapL2promotion, CUtensorMapFloatOOBfill);

void enc2d(EncodeFn fn, CUtensorMap* m, const void* base, uint64_t cols, uint64_t rows, uint32_t bc, uint32_t br) {
  cuuint64_t gd[2] = {cols, rows}, gs[1] = {cols * 2};
  cuuint32_t bd[2] = {bc, br}, es[2] = {1, 1};
  fn(m, CU_TENSOR_MAP_DATA_TYPE_BFLOAT16, 2, const_cast<void*>(base), gd, gs, bd, es, CU_TENSOR_MAP_INTERLEAVE_NONE,
     bc == 64 ? CU_TENSOR_MAP_SWIZZLE_128B : CU_TENSOR_MAP_SWIZZLE_64B, CU_TENSOR_MAP_L2_PROMOTION_L2_128B, CU_TENSOR_MAP_FLOAT_OOB_FILL_NONE);
}

}

extern "C" void kernel_launch(void* const* d_in, const int* in_sizes, int n_in, void* d_out, int out_size) {
  (void)in_sizes; (void)n_in; (void)out_size;
  static EncodeFn fn = nullptr;
  static void *po = nullptr, *ph = nullptr;
  if (!fn) {
    void* p = nullptr;
    cudaDriverEntryPointQueryResult q;
    cudaGetDriverEntryPoint("cuTensorMapEncodeTiled", &p, cudaEnableDefault, &q);
    fn = (EncodeFn)p;
    cudaFuncSetAttribute(fused_block_kernel, cudaFuncAttributeMaxDynamicSharedMemorySize, SMEM_BYTES);
    cudaGetSymbolAddress(&po, g_o);
    cudaGetSymbolAddress(&ph, g_h);
  }
  Params P;
  P.x = (const __nv_bfloat16*)d_in[0];
  P.wqkv = (const __nv_bfloat16*)d_in[1];
  P.wphi = (const __nv_bfloat16*)d_in[2];
  P.wo = (const __nv_bfloat16*)d_in[3];
  P.w1 = (const __nv_bfloat16*)d_in[5];
  P.b1 = (const __nv_bfloat16*)d_in[6];
  P.w2 = (const __nv_bfloat16*)d_in[7];
  P.b2 = (const __nv_bfloat16*)d_in[8];
  P.out = (__nv_bfloat16*)d_out;
  P.d128 = desc64(SB, 16, 1024, 1);
  P.d64 = desc64(SB, 16, 512, 2);
  P.dwphi = desc64(A_WPHI, 128, 1280, 0);
  P.dkvb = desc64(A_KVB, 128, 2304, 0);
  P.dphi = desc64(A_PHI, 16, 1024, 1);
  P.dv = desc64(A_V, 128, 2048, 0);
  enc2d(fn, &P.tq64, P.wqkv, 3 * D_, D_, 64, 96);
  enc2d(fn, &P.tq32, P.wqkv, 3 * D_, D_, 32, 192);
  enc2d(fn, &P.to64, P.wo, D_, D_, 64, 96);
  enc2d(fn, &P.to32, P.wo, D_, D_, 32, 192);
  enc2d(fn, &P.tw1, P.w1, F_, D_, 64, 96);
  enc2d(fn, &P.tw2, P.w2, D_, F_, 64, 96);
  enc2d(fn, &P.tout, P.out, D_, S_, 64, 16);
  {
    cuuint64_t gd[3] = {64, (cuuint64_t)S_, 9}, gs[2] = {D_ * 2, 128};
    cuuint32_t bd[3] = {64, 64, 3}, es[3] = {1, 1, 1};
    fn(&P.tx, CU_TENSOR_MAP_DATA_TYPE_BFLOAT16, 3, const_cast<__nv_bfloat16*>(P.x), gd, gs, bd, es, CU_TENSOR_MAP_INTERLEAVE_NONE,
       CU_TENSOR_MAP_SWIZZLE_128B, CU_TENSOR_MAP_L2_PROMOTION_L2_128B, CU_TENSOR_MAP_FLOAT_OOB_FILL_NONE);
  }
  for (int i = 0; i < 2; i++) {
    cuuint64_t gd[3] = {256, 18, 128}, gs[2] = {1024, 18432};
    cuuint32_t bd[3] = {256, 3, 4}, es[3] = {1, 1, 1};
    fn(i ? &P.tgh : &P.tgo, CU_TENSOR_MAP_DATA_TYPE_UINT32, 3, i ? ph : po, gd, gs, bd, es, CU_TENSOR_MAP_INTERLEAVE_NONE,
       CU_TENSOR_MAP_SWIZZLE_NONE, CU_TENSOR_MAP_L2_PROMOTION_L2_128B, CU_TENSOR_MAP_FLOAT_OOB_FILL_NONE);
  }
  fused_block_kernel<<<128, 384, SMEM_BYTES>>>(P);
}
```

```cpp
#include <cuda_runtime.h>
#include <cuda.h>
#include <cuda_bf16.h>
#include <stdint.h>
#include <type_traits>

namespace {

constexpr int S_ = 2048, D_ = 576, F_ = 4608;
constexpr int NSLOT = 8, SLOT_BYTES = 12288;
constexpr uint32_t SB       = 1024;
constexpr uint32_t A_X      = SB + NSLOT * SLOT_BYTES;
constexpr uint32_t A_XT     = A_X - 16384;
constexpr uint32_t A_PHI    = A_X;
constexpr uint32_t A_V      = A_X + 65536;
constexpr uint32_t A_WPHI   = A_X + 90112;
constexpr uint32_t A_KVB    = A_X + 101632;
constexpr uint32_t A_B1     = A_X + 131072;
constexpr uint32_t A_FULL   = A_B1 + 2304;
constexpr uint32_t A_EMPTY  = A_FULL + 64;
constexpr uint32_t A_LAND   = A_FULL + 128;
constexpr uint32_t A_XFREE  = A_LAND + 80;
constexpr uint32_t A_KVL    = A_XFREE + 8;
constexpr uint32_t A_OUTRDY = A_KVL + 8;
constexpr uint32_t A_TS     = A_OUTRDY + 8;
constexpr uint32_t SMEM_BYTES = A_TS + 256 - SB;
static_assert((A_FULL & 63) == 0, "barrier block alignment");
constexpr int SPIN_LIMIT = 1 << 20;

enum { BAR_INIT = 1, BAR_PREP = 2, BAR_KVIN = 3, BAR_KVOUT = 4, BAR_KVB = 5, BAR_HELP = 6, BAR_WG = 7  , BAR_OMMA = 9 };

struct Params {
  CUtensorMap tx, tq64, tq32, to64, to32, tw1, tw2, tw1b, tw2b, tout, tgo, tgh;
  const __nv_bfloat16 *x, *wqkv, *wphi, *wo, *w1, *b1, *w2, *b2;
  __nv_bfloat16* out;
  uint64_t d128, d128w, d64, dwphi, dkvb, dphi, dv;
};

__device__ uint4    g_o[128 * 36 * 32];
__device__ uint4    g_h[128 * 36 * 32];
__device__ float4   g_stats[128 * 64];
__device__ float4   g_kv[2 * 8 * 720];
__device__ unsigned g_cnt[(8 + 32 + 32 + 16) * 32];
__device__ unsigned g_epoch[128];
#define TSX(t, i)
#define TS(i)
#define TSG(i)
#define TS_DUMP()

__device__ __forceinline__ void mbar_init(uint32_t bar, uint32_t cnt) { asm volatile("mbarrier.init.shared::cta.b64 [%0], %1;" ::"r"(bar), "r"(cnt)); }
__device__ __forceinline__ void mbar_expect_tx(uint32_t bar, uint32_t bytes) { asm volatile("mbarrier.arrive.expect_tx.shared::cta.b64 _, [%0], %1;" ::"r"(bar), "r"(bytes) : "memory"); }
__device__ __forceinline__ void mbar_arrive(uint32_t bar) { asm volatile("mbarrier.arrive.shared::cta.b64 _, [%0];" ::"r"(bar) : "memory"); }
__device__ __forceinline__ void mbar_wait(uint32_t bar, uint32_t parity) {
  asm volatile(
      "{\n.reg .pred p;\n"
      "WAIT_%=:\n"
      "mbarrier.try_wait.parity.shared::cta.b64 p, [%0], %1;\n"
      "@p bra DONE_%=;\n"
      "bra WAIT_%=;\n"
      "DONE_%=:\n}\n" ::"r"(bar), "r"(parity) : "memory");
}
template <int ID, int N> __device__ __forceinline__ void bar_sync() { asm volatile("bar.sync %0, %1;" ::"n"(ID), "n"(N) : "memory"); }
template <int ID, int N> __device__ __forceinline__ void bar_arrive() { asm volatile("bar.arrive %0, %1;" ::"n"(ID), "n"(N) : "memory"); }
__device__ __forceinline__ void bar_sync_wg(int wg) { asm volatile("bar.sync %0, 128;" ::"r"(BAR_WG + wg) : "memory"); }
__device__ __forceinline__ void fence_async_smem() { asm volatile("fence.proxy.async.shared::cta;" ::: "memory"); }
__device__ __forceinline__ void fence_async_global() { asm volatile("fence.proxy.async.global;" ::: "memory"); }
__device__ __forceinline__ void tma2d(uint32_t dst, const CUtensorMap* m, int c0, int c1, uint32_t bar) {
  asm volatile("cp.async.bulk.tensor.2d.shared::cluster.global.mbarrier::complete_tx::bytes [%0], [%1, {%3, %4}], [%2];" ::"r"(dst), "l"(m), "r"(bar), "r"(c0), "r"(c1) : "memory");
}
__device__ __forceinline__ void tma3d(uint32_t dst, const CUtensorMap* m, int c1, int c2, uint32_t bar) {
  asm volatile("cp.async.bulk.tensor.3d.shared::cluster.global.mbarrier::complete_tx::bytes [%0], [%1, {%5, %3, %4}], [%2];" ::"r"(dst), "l"(m), "r"(bar), "r"(c1), "r"(c2), "r"(0) : "memory");
}
__device__ __forceinline__ void bulk_load(uint32_t dst, const void* src, uint32_t bytes, uint32_t bar) {
  asm volatile("cp.async.bulk.shared::cluster.global.mbarrier::complete_tx::bytes [%0], [%1], %2, [%3];" ::"r"(dst), "l"(src), "r"(bytes), "r"(bar) : "memory");
}
__device__ __forceinline__ void bulk_store(void* dst, uint32_t src, uint32_t bytes) {
  asm volatile("cp.async.bulk.global.shared::cta.bulk_group [%0], [%1], %2;" ::"l"(dst), "r"(src), "r"(bytes) : "memory");
}
__device__ __forceinline__ void bulk_commit() { asm volatile("cp.async.bulk.commit_group;" ::: "memory"); }
__device__ __forceinline__ void bulk_wait_all() { asm volatile("cp.async.bulk.wait_group 0;" ::: "memory"); }
__device__ __forceinline__ void l2_prefetch(const void* p, uint32_t bytes) { asm volatile("cp.async.bulk.prefetch.L2.global [%0], %1;" ::"l"(p), "r"(bytes) : "memory"); }
__device__ __forceinline__ void wg_fence() { asm volatile("wgmma.fence.sync.aligned;" ::: "memory"); }
__device__ __forceinline__ void wg_commit() { asm volatile("wgmma.commit_group.sync.aligned;" ::: "memory"); }
template <int N> __device__ __forceinline__ void wg_wait() { asm volatile("wgmma.wait_group.sync.aligned %0;" ::"n"(N) : "memory"); }
template <int N> __device__ __forceinline__ void pin(float (&d)[N]) {
#pragma unroll
  for (int i = 0; i < N; i++) asm volatile("" : "+f"(d[i])::"memory");
}
__device__ __forceinline__ uint32_t pack2(float lo, float hi) { uint32_t r; asm("cvt.rn.bf16x2.f32 %0, %1, %2;" : "=r"(r) : "f"(hi), "f"(lo)); return r; }
__device__ __forceinline__ float bf_lo(uint32_t v) { return __uint_as_float(v << 16); }
__device__ __forceinline__ float bf_hi(uint32_t v) { return __uint_as_float(v & 0xffff0000u); }
__device__ __forceinline__ uint32_t hsub2(uint32_t a, uint32_t b) { uint32_t r; asm("sub.rn.bf16x2 %0, %1, %2;" : "=r"(r) : "r"(a), "r"(b)); return r; }
__device__ __forceinline__ uint32_t hadd2(uint32_t a, uint32_t b) { uint32_t r; asm("add.rn.bf16x2 %0, %1, %2;" : "=r"(r) : "r"(a), "r"(b)); return r; }
__device__ __forceinline__ float ex2(float x) { float r; asm("ex2.approx.ftz.f32 %0, %1;" : "=f"(r) : "f"(x)); return r; }
__device__ __forceinline__ float rcp(float x) { float r; asm("rcp.approx.ftz.f32 %0, %1;" : "=f"(r) : "f"(x)); return r; }
__device__ __forceinline__ float rsq(float x) { float r; asm("rsqrt.approx.ftz.f32 %0, %1;" : "=f"(r) : "f"(x)); return r; }
__device__ __forceinline__ float tanh_(float x) { float r; asm("tanh.approx.f32 %0, %1;" : "=f"(r) : "f"(x)); return r; }
__device__ __forceinline__ void mma16816(float (&d)[4], uint32_t a0, uint32_t a1, uint32_t a2, uint32_t a3, uint32_t b0, uint32_t b1) {
  asm("mma.sync.aligned.m16n8k16.row.col.f32.bf16.bf16.f32 {%0,%1,%2,%3}, {%4,%5,%6,%7}, {%8,%9}, {%0,%1,%2,%3};"
      : "+f"(d[0]), "+f"(d[1]), "+f"(d[2]), "+f"(d[3]) : "r"(a0), "r"(a1), "r"(a2), "r"(a3), "r"(b0), "r"(b1));
}
__device__ __forceinline__ void mma1688(float (&d)[4], uint32_t a0, uint32_t a1, uint32_t b0) {
  asm("mma.sync.aligned.m16n8k8.row.col.f32.bf16.bf16.f32 {%0,%1,%2,%3}, {%4,%5}, {%6}, {%0,%1,%2,%3};"
      : "+f"(d[0]), "+f"(d[1]), "+f"(d[2]), "+f"(d[3]) : "r"(a0), "r"(a1), "r"(b0));
}
__device__ __forceinline__ void sts32(uint32_t a, uint32_t v) { asm volatile("st.shared.b32 [%0], %1;" ::"r"(a), "r"(v) : "memory"); }
__device__ __forceinline__ void sts64(uint32_t a, uint32_t v0, uint32_t v1) { asm volatile("st.shared.v2.b32 [%0], {%1,%2};" ::"r"(a), "r"(v0), "r"(v1) : "memory"); }
__device__ __forceinline__ void sts128(uint32_t a, uint32_t v0, uint32_t v1, uint32_t v2, uint32_t v3) { asm volatile("st.shared.v4.b32 [%0], {%1,%2,%3,%4};" ::"r"(a), "r"(v0), "r"(v1), "r"(v2), "r"(v3) : "memory"); }
__device__ __forceinline__ void lds64(uint32_t a, uint32_t& v0, uint32_t& v1) { asm volatile("ld.shared.v2.b32 {%0,%1}, [%2];" : "=r"(v0), "=r"(v1) : "r"(a) : "memory"); }
__device__ __forceinline__ void lds128(uint32_t a, uint32_t& v0, uint32_t& v1, uint32_t& v2, uint32_t& v3) { asm volatile("ld.shared.v4.b32 {%0,%1,%2,%3}, [%4];" : "=r"(v0), "=r"(v1), "=r"(v2), "=r"(v3) : "r"(a) : "memory"); }
__device__ __forceinline__ void ldsm4(uint32_t a, uint32_t& v0, uint32_t& v1, uint32_t& v2, uint32_t& v3) { asm volatile("ldmatrix.sync.aligned.m8n8.x4.shared.b16 {%0,%1,%2,%3}, [%4];" : "=r"(v0), "=r"(v1), "=r"(v2), "=r"(v3) : "r"(a) : "memory"); }
__device__ __forceinline__ void ldg128(const void* p, uint32_t& v0, uint32_t& v1, uint32_t& v2, uint32_t& v3) { asm volatile("ld.global.cg.v4.b32 {%0,%1,%2,%3}, [%4];" : "=r"(v0), "=r"(v1), "=r"(v2), "=r"(v3) : "l"(p) : "memory"); }
__device__ __forceinline__ void ldg64(const void* p, uint32_t& v0, uint32_t& v1) { asm volatile("ld.global.cg.v2.b32 {%0,%1}, [%2];" : "=r"(v0), "=r"(v1) : "l"(p) : "memory"); }
__device__ __forceinline__ uint32_t ldg32(const void* p) { uint32_t v; asm volatile("ld.global.b32 %0, [%1];" : "=r"(v) : "l"(p) : "memory"); return v; }
__device__ __forceinline__ void stg32(void* p, uint32_t v) { asm volatile("st.global.b32 [%0], %1;" ::"l"(p), "r"(v) : "memory"); }
__device__ __forceinline__ void signal(unsigned* c) { asm volatile("red.relaxed.gpu.global.add.u32 [%0], 1;" ::"l"(c) : "memory"); }
__device__ __forceinline__ void signal_release(unsigned* c) { asm volatile("red.release.gpu.global.add.u32 [%0], 1;" ::"l"(c) : "memory"); }
__device__ __forceinline__ void poll(const unsigned* c, unsigned target) {
  unsigned v; int n = 0;
  do { asm volatile("ld.relaxed.gpu.global.u32 %0, [%1];" : "=r"(v) : "l"(c) : "memory"); } while ((int)(v - target) < 0 && ++n < SPIN_LIMIT);
}

template <int INC, int SCALE_D>
__device__ __forceinline__ void wgmma_rs(float (&d)[16], uint32_t a0, uint32_t a1, uint32_t a2, uint32_t a3, uint64_t& bd) {
  asm volatile("{\n.reg .pred p;\nsetp.ne.b32 p, %22, 0;\n"
    "wgmma.mma_async.sync.aligned.m64n32k16.f32.bf16.bf16 {%0, %1, %2, %3, %4, %5, %6, %7, %8, %9, %10, %11, %12, %13, %14, %15}, {%17, %18, %19, %20}, %16, p, 1, 1, 1;\n"
    "add.s64 %16, %16, %21;\n}\n"
    : "+f"(d[0]), "+f"(d[1]), "+f"(d[2]), "+f"(d[3]), "+f"(d[4]), "+f"(d[5]), "+f"(d[6]), "+f"(d[7]), "+f"(d[8]), "+f"(d[9]), "+f"(d[10]), "+f"(d[11]), "+f"(d[12]), "+f"(d[13]), "+f"(d[14]), "+f"(d[15]), "+l"(bd)
    : "r"(a0), "r"(a1), "r"(a2), "r"(a3), "n"(INC), "n"(SCALE_D));
}
template <int INC, int SCALE_D>
__device__ __forceinline__ void wgmma_rs(float (&d)[20], uint32_t a0, uint32_t a1, uint32_t a2, uint32_t a3, uint64_t& bd) {
  asm volatile("{\n.reg .pred p;\nsetp.ne.b32 p, %26, 0;\n"
    "wgmma.mma_async.sync.aligned.m64n40k16.f32.bf16.bf16 {%0, %1, %2, %3, %4, %5, %6, %7, %8, %9, %10, %11, %12, %13, %14, %15, %16, %17, %18, %19}, {%21, %22, %23, %24}, %20, p, 1, 1, 1;\n"
    "add.s64 %20, %20, %25;\n}\n"
    : "+f"(d[0]), "+f"(d[1]), "+f"(d[2]), "+f"(d[3]), "+f"(d[4]), "+f"(d[5]), "+f"(d[6]), "+f"(d[7]), "+f"(d[8]), "+f"(d[9]), "+f"(d[10]), "+f"(d[11]), "+f"(d[12]), "+f"(d[13]), "+f"(d[14]), "+f"(d[15]), "+f"(d[16]), "+f"(d[17]), "+f"(d[18]), "+f"(d[19]), "+l"(bd)
    : "r"(a0), "r"(a1), "r"(a2), "r"(a3), "n"(INC), "n"(SCALE_D));
}
template <int INC, int SCALE_D>
__device__ __forceinline__ void wgmma_rs(float (&d)[32], uint32_t a0, uint32_t a1, uint32_t a2, uint32_t a3, uint64_t& bd) {
  asm volatile("{\n.reg .pred p;\nsetp.ne.b32 p, %38, 0;\n"
    "wgmma.mma_async.sync.aligned.m64n64k16.f32.bf16.bf16 {%0, %1, %2, %3, %4, %5, %6, %7, %8, %9, %10, %11, %12, %13, %14, %15, %16, %17, %18, %19, %20, %21, %22, %23, %24, %25, %26, %27, %28, %29, %30, %31}, {%33, %34, %35, %36}, %32, p, 1, 1, 1;\n"
    "add.s64 %32, %32, %37;\n}\n"
    : "+f"(d[0]), "+f"(d[1]), "+f"(d[2]), "+f"(d[3]), "+f"(d[4]), "+f"(d[5]), "+f"(d[6]), "+f"(d[7]), "+f"(d[8]), "+f"(d[9]), "+f"(d[10]), "+f"(d[11]), "+f"(d[12]), "+f"(d[13]), "+f"(d[14]), "+f"(d[15]), "+f"(d[16]), "+f"(d[17]), "+f"(d[18]), "+f"(d[19]), "+f"(d[20]), "+f"(d[21]), "+f"(d[22]), "+f"(d[23]), "+f"(d[24]), "+f"(d[25]), "+f"(d[26]), "+f"(d[27]), "+f"(d[28]), "+f"(d[29]), "+f"(d[30]), "+f"(d[31]), "+l"(bd)
    : "r"(a0), "r"(a1), "r"(a2), "r"(a3), "n"(INC), "n"(SCALE_D));
}
template <int INC, int SCALE_D>
__device__ __forceinline__ void wgmma_rs(float (&d)[36], uint32_t a0, uint32_t a1, uint32_t a2, uint32_t a3, uint64_t& bd) {
  asm volatile("{\n.reg .pred p;\nsetp.ne.b32 p, %42, 0;\n"
    "wgmma.mma_async.sync.aligned.m64n72k16.f32.bf16.bf16 {%0, %1, %2, %3, %4, %5, %6, %7, %8, %9, %10, %11, %12, %13, %14, %15, %16, %17, %18, %19, %20, %21, %22, %23, %24, %25, %26, %27, %28, %29, %30, %31, %32, %33, %34, %35}, {%37, %38, %39, %40}, %36, p, 1, 1, 1;\n"
    "add.s64 %36, %36, %41;\n}\n"
    : "+f"(d[0]), "+f"(d[1]), "+f"(d[2]), "+f"(d[3]), "+f"(d[4]), "+f"(d[5]), "+f"(d[6]), "+f"(d[7]), "+f"(d[8]), "+f"(d[9]), "+f"(d[10]), "+f"(d[11]), "+f"(d[12]), "+f"(d[13]), "+f"(d[14]), "+f"(d[15]), "+f"(d[16]), "+f"(d[17]), "+f"(d[18]), "+f"(d[19]), "+f"(d[20]), "+f"(d[21]), "+f"(d[22]), "+f"(d[23]), "+f"(d[24]), "+f"(d[25]), "+f"(d[26]), "+f"(d[27]), "+f"(d[28]), "+f"(d[29]), "+f"(d[30]), "+f"(d[31]), "+f"(d[32]), "+f"(d[33]), "+f"(d[34]), "+f"(d[35]), "+l"(bd)
    : "r"(a0), "r"(a1), "r"(a2), "r"(a3), "n"(INC), "n"(SCALE_D));
}
template <int INC, int SCALE_D>
__device__ __forceinline__ void wgmma_rs(float (&d)[44], uint32_t a0, uint32_t a1, uint32_t a2, uint32_t a3, uint64_t& bd) {
  asm volatile("{\n.reg .pred p;\nsetp.ne.b32 p, %50, 0;\n"
    "wgmma.mma_async.sync.aligned.m64n88k16.f32.bf16.bf16 {%0, %1, %2, %3, %4, %5, %6, %7, %8, %9, %10, %11, %12, %13, %14, %15, %16, %17, %18, %19, %20, %21, %22, %23, %24, %25, %26, %27, %28, %29, %30, %31, %32, %33, %34, %35, %36, %37, %38, %39, %40, %41, %42, %43}, {%45, %46, %47, %48}, %44, p, 1, 1, 1;\n"
    "add.s64 %44, %44, %49;\n}\n"
    : "+f"(d[0]), "+f"(d[1]), "+f"(d[2]), "+f"(d[3]), "+f"(d[4]), "+f"(d[5]), "+f"(d[6]), "+f"(d[7]), "+f"(d[8]), "+f"(d[9]), "+f"(d[10]), "+f"(d[11]), "+f"(d[12]), "+f"(d[13]), "+f"(d[14]), "+f"(d[15]), "+f"(d[16]), "+f"(d[17]), "+f"(d[18]), "+f"(d[19]), "+f"(d[20]), "+f"(d[21]), "+f"(d[22]), "+f"(d[23]), "+f"(d[24]), "+f"(d[25]), "+f"(d[26]), "+f"(d[27]), "+f"(d[28]), "+f"(d[29]), "+f"(d[30]), "+f"(d[31]), "+f"(d[32]), "+f"(d[33]), "+f"(d[34]), "+f"(d[35]), "+f"(d[36]), "+f"(d[37]), "+f"(d[38]), "+f"(d[39]), "+f"(d[40]), "+f"(d[41]), "+f"(d[42]), "+f"(d[43]), "+l"(bd)
    : "r"(a0), "r"(a1), "r"(a2), "r"(a3), "n"(INC), "n"(SCALE_D));
}
template <int INC, int SCALE_D>
__device__ __forceinline__ void wgmma_rs(float (&d)[64], uint32_t a0, uint32_t a1, uint32_t a2, uint32_t a3, uint64_t& bd) {
  asm volatile("{\n.reg .pred p;\nsetp.ne.b32 p, %70, 0;\n"
    "wgmma.mma_async.sync.aligned.m64n128k16.f32.bf16.bf16 {%0, %1, %2, %3, %4, %5, %6, %7, %8, %9, %10, %11, %12, %13, %14, %15, %16, %17, %18, %19, %20, %21, %22, %23, %24, %25, %26, %27, %28, %29, %30, %31, %32, %33, %34, %35, %36, %37, %38, %39, %40, %41, %42, %43, %44, %45, %46, %47, %48, %49, %50, %51, %52, %53, %54, %55, %56, %57, %58, %59, %60, %61, %62, %63}, {%65, %66, %67, %68}, %64, p, 1, 1, 1;\n"
    "add.s64 %64, %64, %69;\n}\n"
    : "+f"(d[0]), "+f"(d[1]), "+f"(d[2]), "+f"(d[3]), "+f"(d[4]), "+f"(d[5]), "+f"(d[6]), "+f"(d[7]), "+f"(d[8]), "+f"(d[9]), "+f"(d[10]), "+f"(d[11]), "+f"(d[12]), "+f"(d[13]), "+f"(d[14]), "+f"(d[15]), "+f"(d[16]), "+f"(d[17]), "+f"(d[18]), "+f"(d[19]), "+f"(d[20]), "+f"(d[21]), "+f"(d[22]), "+f"(d[23]), "+f"(d[24]), "+f"(d[25]), "+f"(d[26]), "+f"(d[27]), "+f"(d[28]), "+f"(d[29]), "+f"(d[30]), "+f"(d[31]), "+f"(d[32]), "+f"(d[33]), "+f"(d[34]), "+f"(d[35]), "+f"(d[36]), "+f"(d[37]), "+f"(d[38]), "+f"(d[39]), "+f"(d[40]), "+f"(d[41]), "+f"(d[42]), "+f"(d[43]), "+f"(d[44]), "+f"(d[45]), "+f"(d[46]), "+f"(d[47]), "+f"(d[48]), "+f"(d[49]), "+f"(d[50]), "+f"(d[51]), "+f"(d[52]), "+f"(d[53]), "+f"(d[54]), "+f"(d[55]), "+f"(d[56]), "+f"(d[57]), "+f"(d[58]), "+f"(d[59]), "+f"(d[60]), "+f"(d[61]), "+f"(d[62]), "+f"(d[63]), "+l"(bd)
    : "r"(a0), "r"(a1), "r"(a2), "r"(a3), "n"(INC), "n"(SCALE_D));
}
template <int INCA, int INCB, int SCALE_D>
__device__ __forceinline__ void wgmma_ss_tt(float (&d)[12], uint64_t& ad, uint64_t& bd) {
  asm volatile("{\n.reg .pred p;\nsetp.ne.b32 p, %16, 0;\n"
    "wgmma.mma_async.sync.aligned.m64n24k16.f32.bf16.bf16 {%0, %1, %2, %3, %4, %5, %6, %7, %8, %9, %10, %11}, %12, %13, p, 1, 1, 1, 1;\n"
    "add.s64 %12, %12, %14;\nadd.s64 %13, %13, %15;\n}\n"
    : "+f"(d[0]), "+f"(d[1]), "+f"(d[2]), "+f"(d[3]), "+f"(d[4]), "+f"(d[5]), "+f"(d[6]), "+f"(d[7]), "+f"(d[8]), "+f"(d[9]), "+f"(d[10]), "+f"(d[11]), "+l"(ad), "+l"(bd)
    : "n"(INCA), "n"(INCB), "n"(SCALE_D));
}

__host__ __device__ constexpr uint32_t desc_lo(uint32_t addr, uint32_t lbo) { return ((addr & 0x3FFFF) >> 4) | ((lbo >> 4) << 16); }
__host__ __device__ constexpr uint32_t desc_hi(uint32_t sbo, uint32_t swz) { return (sbo >> 4) | (swz << 30); }
__host__ __device__ constexpr uint64_t desc64(uint32_t addr, uint32_t lbo, uint32_t sbo, uint32_t swz) { return ((uint64_t)desc_hi(sbo, swz) << 32) | desc_lo(addr, lbo); }
template <uint32_t OFF> __device__ __forceinline__ uint64_t dadd(uint64_t base) {
  uint64_t d;
  asm volatile("add.s64 %0, %1, %2;" : "=l"(d) : "l"(base), "n"(OFF));
  return d;
}
template <int I, int N, class F> __device__ __forceinline__ void static_for(F f) {
  if constexpr (I < N) { f(std::integral_constant<int, I>{}); static_for<I + 1, N>(f); }
}

template <int KS, int K0, int ROWB, int NA>
__device__ __forceinline__ void stage_issue(float (&acc)[NA], const uint32_t (&a)[144], uint64_t d) {
  wg_fence();
  static_for<0, KS>([&](auto kk) {
    constexpr int k = K0 + kk.value;
    wgmma_rs<ROWB, k != 0>(acc, a[4 * k], a[4 * k + 1], a[4 * k + 2], a[4 * k + 3], d);
  });
  wg_commit();
}
template <int KS, int K0, int ROWB, int IT, int NA>
__device__ __forceinline__ void stage_c(float (&acc)[NA], const uint32_t (&a)[144], uint64_t base) {
  constexpr uint32_t slot = IT & (NSLOT - 1);
  mbar_wait(A_FULL + 8 * slot, (IT >> 3) & 1);
  stage_issue<KS, K0, ROWB>(acc, a, dadd<slot * (SLOT_BYTES / 16)>(base));
}
template <int IT> __device__ __forceinline__ void release_c(int lane) {
  if (lane == 0) mbar_arrive(A_EMPTY + 8 * (IT & (NSLOT - 1)));
}
template <int K0>
__device__ __forceinline__ void stage_r(float (&acc)[64], const uint32_t (&a)[144], uint32_t t8, uint64_t base) {
  const uint32_t s8 = t8 & 56;
  mbar_wait(A_FULL + s8, (t8 >> 6) & 1);
  stage_issue<3, K0, 128>(acc, a, base + s8 * (SLOT_BYTES / 128));
}
__device__ __forceinline__ void release_r(uint32_t t8, int lane) {
  if (lane == 0) mbar_arrive(A_EMPTY + (t8 & 56));
}

template <int HI, int NEG>
__device__ __forceinline__ void softmax18(const float (&p)[36], uint32_t (&w)[9]) {
  constexpr float L2E = NEG ? -1.4426950408889634f : 1.4426950408889634f;
  float m = p[2 * HI];
#pragma unroll
  for (int i = 1; i < 18; i++) { const float v = p[4 * (i >> 1) + 2 * HI + (i & 1)]; m = NEG ? fminf(m, v) : fmaxf(m, v); }
  m *= -L2E;
  float e[18], s = 0.f;
#pragma unroll
  for (int i = 0; i < 18; i++) { e[i] = ex2(fmaf(p[4 * (i >> 1) + 2 * HI + (i & 1)], L2E, m)); s += e[i]; }
  s = rcp(s);
#pragma unroll
  for (int t = 0; t < 9; t++) w[t] = pack2(e[2 * t] * s, e[2 * t + 1] * s);
}
template <int HI, int NEG>
__device__ __forceinline__ void phik_piece(const float (&p)[36], uint32_t rowaddr, int c, int t7) {
  uint32_t w[9];
  softmax18<HI, NEG>(p, w);
  rowaddr += HI * 1024;
  sts128(rowaddr + ((((2 * NEG + 2 * c) & 7) ^ t7) << 4), w[0], w[1], w[2], w[3]);
  sts128(rowaddr + ((((2 * NEG + 1 + 2 * c) & 7) ^ t7) << 4), w[4], w[5], w[6], w[7]);
  sts32(rowaddr + ((((4 + 2 * c) & 7) ^ t7) << 4) + 4 * NEG, w[8]);
}
template <int HI, int NEG>
__device__ __forceinline__ void phiq_piece(const float (&p)[36], uint32_t (&fq)[36]) {
  uint32_t w[9];
  softmax18<HI, NEG>(p, w);
#pragma unroll
  for (int t = 0; t < 8; t++) fq[2 * (8 * NEG + t) + HI] = w[t];
  fq[2 * (16 + NEG) + HI] = w[8];
}

__device__ __forceinline__ void phi_mma0(float (&p)[36], const float (&a32)[16], float rlo, float rhi, uint64_t d) {
  uint32_t f[8];
#pragma unroll
  for (int j = 0; j < 4; j++) { f[2 * j] = pack2(a32[4 * j] * rlo, a32[4 * j + 1] * rlo); f[2 * j + 1] = pack2(a32[4 * j + 2] * rhi, a32[4 * j + 3] * rhi); }
  wg_fence();
  static_for<0, 2>([&](auto s) { wgmma_rs<16, s.value != 0>(p, f[4 * s.value], f[4 * s.value + 1], f[4 * s.value + 2], f[4 * s.value + 3], d); });
  wg_commit();
}
__device__ __forceinline__ void phi_mma1(float (&p)[36], const float (&a40)[20], float rlo, float rhi, uint64_t d) {
  uint32_t f[12];
#pragma unroll
  for (int j = 0; j < 5; j++) { f[2 * j] = pack2(a40[4 * j] * rlo, a40[4 * j + 1] * rlo); f[2 * j + 1] = pack2(a40[4 * j + 2] * rhi, a40[4 * j + 3] * rhi); }
  f[10] = 0; f[11] = 0;
  d = dadd<32>(d);
  wg_fence();
  static_for<0, 3>([&](auto s) { wgmma_rs<16, 1>(p, f[4 * s.value], f[4 * s.value + 1], f[4 * s.value + 2], f[4 * s.value + 3], d); });
  wg_commit();
}

__device__ __forceinline__ void stage_piece(uint32_t st, int lane, int odd, const uint32_t (&f)[16], uint32_t s0, uint32_t s1) {
  const uint32_t pf = st + odd * 256 + lane * 16;
#pragma unroll
  for (int s = 0; s < 4; s++) sts128(pf + s * 512, f[4 * s], f[4 * s + 1], f[4 * s + 2], f[4 * s + 3]);
  sts64(st + (odd ? 0 : 2048) + lane * 8, s0, s1);
}
template <int C>
__device__ __forceinline__ void land_read(uint32_t (&a)[144], uint32_t base, int lane) {
  static_for<6 * C, 6 * C + 6>([&](auto s) {
    constexpr int k = s.value;
    constexpr uint32_t o = C * 12288 + (k - 6 * C) * 512;
    if constexpr (k % 9 == 4) { lds64(base + o + lane * 8, a[4 * k], a[4 * k + 1]); lds64(base + o + 256 + lane * 8, a[4 * k + 2], a[4 * k + 3]); }
    else lds128(base + o + lane * 16, a[4 * k], a[4 * k + 1], a[4 * k + 2], a[4 * k + 3]);
  });
}
__device__ __forceinline__ void tail_read(uint32_t (&a)[144], const uint4* blk, int lane) {
  static_for<30, 36>([&](auto s) {
    constexpr int k = s.value;
    if constexpr (k % 9 == 4) {
      const uint2* p = reinterpret_cast<const uint2*>(blk + k * 32) + lane;
      ldg64(p, a[4 * k], a[4 * k + 1]); ldg64(p + 32, a[4 * k + 2], a[4 * k + 3]);
    } else ldg128(blk + k * 32 + lane, a[4 * k], a[4 * k + 1], a[4 * k + 2], a[4 * k + 3]);
  });
}

__device__ __forceinline__ float gelu(float hy) {
  const float t = tanh_(hy * fmaf(hy * hy, 0.285419265090f, 1.595769121606f));
  return fmaf(hy, t, hy);
}
__device__ __forceinline__ void gelu_chunk(uint32_t addr, uint32_t b1addr, float rlo, float rhi) {
  uint32_t y0, y1, y2, y3, b0, b1, b2, b3;
  lds128(addr, y0, y1, y2, y3);
  lds128(b1addr, b0, b1, b2, b3);
  y0 = pack2(gelu(fmaf(bf_lo(y0), rlo, __uint_as_float(b0))), gelu(fmaf(bf_hi(y0), rlo, __uint_as_float(b1))));
  y1 = pack2(gelu(fmaf(bf_lo(y1), rhi, __uint_as_float(b0))), gelu(fmaf(bf_hi(y1), rhi, __uint_as_float(b1))));
  y2 = pack2(gelu(fmaf(bf_lo(y2), rlo, __uint_as_float(b2))), gelu(fmaf(bf_hi(y2), rlo, __uint_as_float(b3))));
  y3 = pack2(gelu(fmaf(bf_lo(y3), rhi, __uint_as_float(b2))), gelu(fmaf(bf_hi(y3), rhi, __uint_as_float(b3))));
  sts128(addr, y0, y1, y2, y3);
}
template <int Q0, int NA>
__device__ __forceinline__ void park4(const float (&acc)[NA], uint32_t addr) {
#pragma unroll
  for (int q = 0; q < 4; q++) {
    const float* v = &acc[8 * (Q0 + q)];
    sts128(addr + q * 512, pack2(v[0], v[1]), pack2(v[2], v[3]), pack2(v[4], v[5]), pack2(v[6], v[7]));
  }
}
template <int Q0, int NA>
__device__ __forceinline__ void out_stage(const float (&acc)[NA], uint32_t st, int lane) {
  const uint32_t ra = st + ((lane & 7) + (lane & 8)) * 128;
  const int x7 = (lane & 7) ^ (lane >> 4);
#pragma unroll
  for (int q = 0; q < 4; q++) {
    const float* v = &acc[8 * (Q0 + q)];
    asm volatile("stmatrix.sync.aligned.m8n8.x4.shared.b16 [%0], {%1,%2,%3,%4};" ::"r"(ra + (((2 * q) ^ x7) << 4)),
                 "r"(pack2(v[0], v[1])), "r"(pack2(v[2], v[3])), "r"(pack2(v[4], v[5])), "r"(pack2(v[6], v[7])) : "memory");
  }
}
__device__ __forceinline__ void out_send(const CUtensorMap* m, uint32_t st, int col, int row) {
  asm volatile("cp.reduce.async.bulk.tensor.2d.global.shared::cta.add.tile.bulk_group [%0, {%2, %3}], [%1];" ::"l"(m), "r"(st), "r"(col), "r"(row) : "memory");
}

__global__ void __launch_bounds__(384, 1) fused_block_kernel(const __grid_constant__ Params P) {
  extern __shared__ __align__(1024) uint8_t smem_raw[];
  if ((uint32_t)__cvta_generic_to_shared(smem_raw) != SB) return;
  const int tid = threadIdx.x, warp = __shfl_sync(0xffffffffu, tid >> 5, 0), lane = __shfl_sync(0xffffffffu, tid & 31, tid & 31);
  const int blk = blockIdx.x;
  int r, g;
  {
    const int q = blk >> 3, u = q >> 1;
    const int R = (u < 4) ? u : 7 - u;
    const int G = ((u >> 2) << 1) | ((q ^ u) & 1);
    r = 4 * R + ((blk & 7) >> 1);
    g = 2 * G + (blk & 1);
  }
  const int odd = g & 1;

  if (warp >= 8) {
    asm volatile("setmaxnreg.dec.sync.aligned.u32 24;");
    if (warp == 8) {
      if (lane == 0) {
#pragma unroll
        for (int s = 0; s < NSLOT; s++) { mbar_init(A_FULL + 8 * s, 1); mbar_init(A_EMPTY + 8 * s, 8); }
        mbar_init(A_XFREE, 8); mbar_init(A_KVL, 1); mbar_init(A_OUTRDY, 1);
        fence_async_smem();
      }
      __syncwarp();
      bar_arrive<BAR_INIT, 384>();
      if (lane == 0) {
        const int c64 = 72 * g + (odd ? -8 : 32), c32 = 72 * g + (odd ? 40 : 0);
#pragma unroll 1
        for (uint32_t it = 0; it < 144; it++) {
          const CUtensorMap* m; int c0, c1;
          if (it < 27) {
            const int sec = it / 9, s = it - 9 * sec, s32 = (sec == 1) ? s - 6 : s, s64 = (sec == 1) ? s : s - 3;
            const bool n32 = (unsigned)s32 < 3u;
            m = n32 ? &P.tq32 : &P.tq64;
            c0 = (sec == 2 ? 0 : (sec + 1) * D_) + (n32 ? c32 : c64);
            c1 = n32 ? 192 * s32 : 96 * s64;
          } else if (it < 36) {
            const int t = (it - 27) / 3, s = it - 27 - 3 * t;
            m = s == 2 ? &P.to32 : &P.to64;
            c0 = s == 2 ? c32 : c64;
            c1 = 192 * t + (s == 1 ? 96 : 0);
          } else if (it < 42 || it >= 138) {
            m = it < 42 ? &P.tw1 : &P.tw2;
            c0 = it < 42 ? D_ * g : 512;
            c1 = it < 42 ? 96 * (it - 36) : D_ * g + 96 * (it - 138);
          } else {
            const int p = (it - 42) / 12, s = it - 42 - 12 * p;
            m = p < 4 ? &P.tw1b : &P.tw2b;
            c0 = p < 4 ? 48 * s : D_ * g + 48 * s;
            c1 = p < 4 ? 9 * g + 1 + 2 * p : 2 * (p - 4);
          }
          const uint32_t slot = it & (NSLOT - 1);
          if (it == 6) mbar_wait(A_XFREE, 0);
          mbar_wait(A_EMPTY + 8 * slot, ((it >> 3) & 1) ^ 1);
          mbar_expect_tx(A_FULL + 8 * slot, SLOT_BYTES);
          if (it >= 42 && it < 138) tma3d(SB + slot * SLOT_BYTES, m, c0, c1, A_FULL + 8 * slot);
          else tma2d(SB + slot * SLOT_BYTES, m, c0, c1, A_FULL + 8 * slot);
        }
      }
    } else {
      const int ht = tid - 288, hw = warp - 9;
      const bool feeder = (hw < 2) && lane == 0;
      const uint32_t lb = A_LAND + hw * 40, H = A_X + hw * 65536;
      if (feeder) {
#pragma unroll
        for (int i = 0; i < 5; i++) mbar_init(lb + 8 * i, 1);
        fence_async_smem();
#pragma unroll
        for (int i = 0; i < 3; i++) { mbar_expect_tx(lb + 8 * i, 24576); tma3d(A_XT + hw * 73728 + i * 24576, &P.tx, r * 128 + hw * 64, 3 * i, lb + 8 * i); }
        mbar_arrive(lb + 24); mbar_arrive(lb + 32);
      }
      if (ht == 64) l2_prefetch(reinterpret_cast<const char*>(P.wqkv) + blk * 15552, 15552);
      const unsigned ep1 = ldg32(&g_epoch[blk]) + 1;
      uint32_t wv[7], bv[3];
      {
        const uint32_t* wp = reinterpret_cast<const uint32_t*>(P.wphi) + g * 648 + ht;
#pragma unroll
        for (int i = 0; i < 7; i++) if (i < 6 || ht < 72) wv[i] = ldg32(wp + 96 * i);
        const uint32_t* bp = reinterpret_cast<const uint32_t*>(P.b1) + g * 288 + ht;
#pragma unroll
        for (int i = 0; i < 3; i++) bv[i] = ldg32(bp + 96 * i);
      }
      bar_sync<BAR_INIT, 384>();
#pragma unroll
      for (int i = 0; i < 3; i++)
        sts64(A_B1 + (ht >> 3) * 64 + (ht & 3) * 16 + (ht & 4) * 2 + i * 768, __float_as_uint(0.5f * bf_lo(bv[i])), __float_as_uint(0.5f * bf_hi(bv[i])));
      if (ht < 45) g_kv[((ep1 & 1) * 8 + g) * 720 + r * 45 + ht] = make_float4(0.f, 0.f, 0.f, 0.f);
      mbar_wait(A_XFREE, 0);
      if (ht == 64) l2_prefetch(reinterpret_cast<const char*>(P.wo) + blk * 5184, 5184);
      if (ht == 65) l2_prefetch(reinterpret_cast<const char*>(P.w1) + blk * 41472, 41472);
      if (ht == 66) l2_prefetch(reinterpret_cast<const char*>(P.w2) + blk * 41472, 41472);
#pragma unroll 1
      for (int i = ht; i < 720; i += 96) sts128(A_WPHI + i * 16, 0, 0, 0, 0);
      bar_sync<BAR_HELP, 96>();
      {
        const int c40 = odd ? 0 : 32, c32 = odd ? 40 : 0;
#pragma unroll
        for (int i = 0; i < 7; i++) {
          const int e = ht + 96 * i, col = e / 9, t = e - col * 9, h = col / 18;
          const int kk = (col >= c40 && col < c40 + 40) ? 32 + col - c40 : col - c32;
          if (i < 6 || ht < 72) sts32(A_WPHI + t * 1280 + kk * 16 + 4 * h, wv[i]);
        }
      }
#pragma unroll 1
      for (int i = ht; i < 512; i += 96) sts128(A_V + (i >> 7) * 6144 + 4096 + (i & 127) * 16, 0, 0x00003f80u, 0, 0);
      fence_async_smem();
      bar_arrive<BAR_PREP, 352>();
#pragma unroll 1
      for (int i = ht; i < 1584; i += 96) sts128(A_KVB + i * 16, 0, 0, 0, 0);
      if (hw == 0) {
        bar_sync<BAR_KVOUT, 288>();
        if (lane == 0) {
          TSX(288, 20);
          float4* kv = g_kv + (((ep1 + 1) & 1) * 8 + g) * 720;
#pragma unroll
          for (int h = 0; h < 4; h++)
            asm volatile("cp.reduce.async.bulk.global.shared::cta.bulk_group.add.f32 [%0], [%1], %2;" ::"l"(kv + h * 180), "r"(A_V + h * 6144), "r"(2880) : "memory");
          bulk_commit();
          mbar_expect_tx(A_KVL, 11520);
          bulk_wait_all();
          signal(&g_cnt[g * 32]);
          TSX(288, 21);
          poll(&g_cnt[g * 32], ep1 * 16);
          TSX(288, 22);
          bulk_load(A_PHI, kv, 11520, A_KVL);
        }
      }
      const int f0 = ht / 5, kq = ht - 5 * f0, f1 = f0 + 18;
      const uint32_t kr0 = A_KVB + (16 * (f0 >> 2) + 8 * ((f0 >> 1) & 1) + (f0 & 1)) * 16, kr1 = A_KVB + (16 * (f1 >> 2) + 8 * ((f1 >> 1) & 1) + (f1 & 1)) * 16;
      bar_sync<BAR_HELP, 96>();
      mbar_wait(A_KVL, 0);
      TSX(288, 23);
      if (ht < 90) {
#pragma unroll
        for (int h = 0; h < 4; h++) {
          const int n0 = 18 * h + 4 * kq, n1 = n0 + 2;
          const uint32_t c0 = (n0 >> 3) * 2304 + (n0 & 7) * 2 + 32 * h, c1 = (n1 >> 3) * 2304 + (n1 & 7) * 2 + 32 * h;
#pragma unroll
          for (int u = 0; u < 2; u++) {
            uint32_t v0, v1, v2, v3;
            lds128(A_PHI + ht * 16 + h * 2880 + u * 1440, v0, v1, v2, v3);
            const uint32_t ra = u ? kr1 : kr0;
            sts32(ra + c0, pack2(__uint_as_float(v0), __uint_as_float(v1)));
            if (kq < 4) sts32(ra + c1, pack2(__uint_as_float(v2), __uint_as_float(v3)));
            else {
              const uint32_t zz = (h & 1) ? pack2(0.f, __uint_as_float(v2)) : pack2(__uint_as_float(v2), 0.f);
              sts128(ra + 32 * h + (9 + (h >> 1)) * 2304, zz, zz, zz, zz);
            }
          }
        }
      }
      fence_async_smem();
      bar_arrive<BAR_KVB, 352>();
      TSX(288, 24);
      if (hw < 2) {
        bar_sync<BAR_OMMA, 320>();
        if (lane == 0) {
#pragma unroll 1
          for (int x = 0; x < 2; x++) {
            poll(&g_cnt[(8 + 32 * x + 2 * r + hw) * 32], ep1 * 32);
            TSX(288, 25 + x);
            mbar_expect_tx(lb, x ? 16384 : 12288);
            if (x) bulk_load(H + 61440, g_stats + (r * 8 + hw * 4) * 64, 4096, lb);
#pragma unroll 1
            for (int i = 0; i < 5; i++) {
              if (i) mbar_expect_tx(lb + 8 * i, 12288);
              tma3d(H + i * 12288, x ? &P.tgh : &P.tgo, 3 * i, r * 8 + hw * 4, lb + 8 * i);
            }
          }
          mbar_wait(lb + 32, 0);
        }
      }
      bar_sync<BAR_HELP, 96>();
#pragma unroll 1
      for (int u = hw; u < 18; u += 3) {
        const int j = u >> 1, w0 = r * 8 + (u & 1) * 4, J = 9 * g + j;
        const bool split = (j == (odd ? 0 : 8));
        const uint2* src = reinterpret_cast<const uint2*>(g_h + (w0 * 36 + (J >> 1)) * 32) + (split ? (J & 1) * 32 + lane : (J & 1) + 2 * lane);
        const int col = 8 * J + 2 * (lane & 3);
        const uint32_t b = ldg32(P.b2 + col);
        uint32_t v[8];
#pragma unroll
        for (int w = 0; w < 4; w++) ldg64(src + w * 2304, v[2 * w], v[2 * w + 1]);
        __nv_bfloat16* o = P.out + (size_t)(w0 * 16 + (lane >> 2)) * D_ + col;
#pragma unroll
        for (int w = 0; w < 8; w++) stg32(o + w * 8 * D_, hadd2(v[w], b));
      }
      bar_sync<BAR_HELP, 96>();
      if (ht == 0) {
        signal_release(&g_cnt[(72 + r) * 32]);
        poll(&g_cnt[(72 + r) * 32], ep1 * 8);
        asm volatile("fence.acq_rel.gpu;" ::: "memory");
        mbar_arrive(A_OUTRDY);
        g_epoch[blk] = ep1;
        TSX(288, 27);
      }
    }
  } else {
    asm volatile("setmaxnreg.inc.sync.aligned.u32 240;");
    TS(0);
    TSG(30);
    const int c = lane & 3, rq = lane >> 2, wg = warp >> 2, wq = warp & 3;
    const uint64_t z = P.d64, o40 = P.d128 + odd;
    const uint32_t lb = A_LAND + wg * 40;
    uint32_t a[144];
    float rlo, rhi;
    bar_sync<BAR_INIT, 384>();
    {
      const uint32_t xr = A_XT + wg * 73728 + (wq * 16 + (lane & 15)) * 128;
      const int x7 = (lane & 7) ^ (lane >> 4);
      float sm[4] = {}, dl[2][4] = {}, dh[2][4] = {};
      static_for<0, 36>([&](auto s) {
        constexpr int k = s.value;
        if constexpr (k % 12 == 0) {
          mbar_wait(lb + 8 * (k / 12), 0);
          static_for<k, k + 12>([&](auto t) {
            constexpr int u = t.value;
            ldsm4(xr + (u >> 2) * 8192 + (((2 * (u & 3)) ^ x7) << 4), a[4 * u], a[4 * u + 1], a[4 * u + 2], a[4 * u + 3]);
          });
        }
        mma16816(sm, a[4 * k], a[4 * k + 1], a[4 * k + 2], a[4 * k + 3], 0x3f803f80u, 0x3f803f80u);
        mma1688(dl[0], a[4 * k], a[4 * k + 1], a[4 * k]);
        mma1688(dh[0], a[4 * k], a[4 * k + 1], a[4 * k + 1]);
        mma1688(dl[1], a[4 * k + 2], a[4 * k + 3], a[4 * k + 2]);
        mma1688(dh[1], a[4 * k + 2], a[4 * k + 3], a[4 * k + 3]);
      });
      const float mlo = sm[0] * (1.f / D_), mhi = sm[2] * (1.f / D_);
      if (lane == 0) asm volatile("mbarrier.arrive.shared::cta.b64 _, [%0];" ::"r"(A_XFREE), "f"(mlo) : "memory");
      float ql = (rq & 1) ? dl[0][1] + dl[1][1] : dl[0][0] + dl[1][0];
      float qh = (rq & 1) ? dh[0][3] + dh[1][3] : dh[0][2] + dh[1][2];
      ql = __shfl_sync(0xffffffffu, ql, (lane & 28) | (rq >> 1));
      qh = __shfl_sync(0xffffffffu, qh, (lane & 28) | (rq >> 1));
      rlo = rsq(fmaxf(ql * (1.f / D_) - mlo * mlo, 0.f) + 1e-5f);
      rhi = rsq(fmaxf(qh * (1.f / D_) - mhi * mhi, 0.f) + 1e-5f);
      const uint32_t ml = pack2(mlo, mlo), mh = pack2(mhi, mhi);
#pragma unroll
      for (int i = 0; i < 144; i++) a[i] = hsub2(a[i], (i & 1) ? mh : ml);
    }
    TS(1);
    uint32_t fq[36];
    {
      float k40[20], k32[16], v40[20], v32[16], p[36];
      stage_c<12, 0, 64, 0>(k32, a, z);
      stage_c<12, 12, 64, 1>(k32, a, z);    wg_wait<1>(); release_c<0>(lane);
      stage_c<12, 24, 64, 2>(k32, a, z);    wg_wait<1>(); release_c<1>(lane);
      stage_c<6, 0, 128, 3>(k40, a, o40);   wg_wait<1>(); pin(k32); release_c<2>(lane);
      stage_c<6, 6, 128, 4>(k40, a, o40);   wg_wait<1>(); release_c<3>(lane);
      stage_c<6, 12, 128, 5>(k40, a, o40);  wg_wait<1>(); release_c<4>(lane);
      stage_c<6, 18, 128, 6>(k40, a, o40);
      bar_sync<BAR_PREP, 352>();
      phi_mma0(p, k32, rlo, rhi, P.dwphi);        wg_wait<1>(); release_c<5>(lane); release_c<6>(lane);
      stage_c<6, 24, 128, 7>(k40, a, o40);
      stage_c<6, 30, 128, 8>(k40, a, o40);  wg_wait<1>(); release_c<7>(lane);
      wg_wait<0>(); pin(k40); release_c<8>(lane);
      TS(2);
      phi_mma1(p, k40, rlo, rhi, P.dwphi);
      stage_c<6, 0, 128, 9>(v40, a, o40);   wg_wait<1>(); pin(p);
      const uint32_t prow = A_PHI + c * 16384 + (warp * 16 + rq) * 128;
      stage_c<6, 6, 128, 10>(v40, a, o40);
      stage_c<6, 12, 128, 11>(v40, a, o40); phik_piece<0, 0>(p, prow, c, rq); wg_wait<1>(); release_c<9>(lane); release_c<10>(lane);
      stage_c<6, 18, 128, 12>(v40, a, o40); phik_piece<0, 1>(p, prow, c, rq); wg_wait<1>(); release_c<11>(lane);
      stage_c<6, 24, 128, 13>(v40, a, o40); phik_piece<1, 0>(p, prow, c, rq); wg_wait<1>(); release_c<12>(lane);
      stage_c<6, 30, 128, 14>(v40, a, o40); phik_piece<1, 1>(p, prow, c, rq); wg_wait<1>(); release_c<13>(lane);
      stage_c<12, 0, 64, 15>(v32, a, z);    wg_wait<1>(); release_c<14>(lane);
      stage_c<12, 12, 64, 16>(v32, a, z);   wg_wait<1>(); release_c<15>(lane);
      stage_c<12, 24, 64, 17>(v32, a, z);   wg_wait<1>(); release_c<16>(lane);
      TS(3);
      stage_c<12, 0, 64, 18>(k32, a, z);    wg_wait<1>(); pin(v40); pin(v32); release_c<17>(lane);
      {
        const int c40 = odd ? 0 : 32, c32 = odd ? 40 : 0;
        const uint32_t vrow = A_V + (warp * 16 + rq) * 16;
#pragma unroll
        for (int j = 0; j < 9; j++) {
          const int col = (j < 5 ? c40 + 8 * j : c32 + 8 * (j - 5)) + 2 * c;
          const int h = (col * 57) >> 10, d = col - 18 * h;
          const uint32_t ad = vrow + h * 6144 + (d >> 3) * 2048 + (d & 7) * 2;
          const float* v = j < 5 ? &v40[4 * j] : &v32[4 * (j - 5)];
          sts32(ad, pack2(v[0] * rlo, v[1] * rlo));
          sts32(ad + 128, pack2(v[2] * rhi, v[3] * rhi));
        }
      }
      fence_async_smem();
      bar_sync<BAR_KVIN, 256>();
      float kv0[12], kv1[12];
      {
        uint64_t da = P.dphi + wg * 2048, db = P.dv + wg * 768;
        wg_fence();
        static_for<0, 8>([&](auto s) { wgmma_ss_tt<128, s.value == 7 ? 384 - 112 : 16, s.value != 0>(kv0, da, db); });
        static_for<0, 8>([&](auto s) { wgmma_ss_tt<128, 16, s.value != 0>(kv1, da, db); });
        wg_commit();
      }
      stage_c<12, 12, 64, 19>(k32, a, z);   wg_wait<1>(); pin(kv0); pin(kv1); release_c<18>(lane);
      bar_sync_wg(wg);
#pragma unroll
      for (int hh = 0; hh < 2; hh++) {
#pragma unroll
        for (int u = 0; u < 2; u++) {
          const int f = 8 * ((2 * wq + u - 4 * wg - 2 * hh) & 7) + rq;
          if (f < 36) {
            const uint32_t ad = A_V + (2 * wg + hh) * 6144 + f * 80 + c * 8;
            const float* kvp = hh ? kv1 : kv0;
            sts64(ad, __float_as_uint(kvp[2 * u]), __float_as_uint(kvp[2 * u + 1]));
            sts64(ad + 32, __float_as_uint(kvp[4 + 2 * u]), __float_as_uint(kvp[5 + 2 * u]));
            if (c < 2) sts64(ad + 64, __float_as_uint(kvp[8 + 2 * u]), __float_as_uint(kvp[9 + 2 * u]));
          }
        }
      }
      fence_async_smem();
      bar_arrive<BAR_KVOUT, 288>();
      stage_c<12, 24, 64, 20>(k32, a, z);   wg_wait<1>(); release_c<19>(lane);
      stage_c<6, 0, 128, 21>(k40, a, o40);  wg_wait<1>(); pin(k32); release_c<20>(lane);
      stage_c<6, 6, 128, 22>(k40, a, o40);
      phi_mma0(p, k32, rlo, rhi, P.dwphi);        wg_wait<1>(); release_c<21>(lane); release_c<22>(lane);
      stage_c<6, 12, 128, 23>(k40, a, o40);
      stage_c<6, 18, 128, 24>(k40, a, o40); wg_wait<1>(); release_c<23>(lane);
      stage_c<6, 24, 128, 25>(k40, a, o40); wg_wait<1>(); release_c<24>(lane);
      stage_c<6, 30, 128, 26>(k40, a, o40); wg_wait<1>(); release_c<25>(lane);
      wg_wait<0>(); pin(k40); release_c<26>(lane);
      TS(4);
      phi_mma1(p, k40, rlo, rhi, P.dwphi);
      wg_wait<0>(); pin(p);
      phiq_piece<0, 0>(p, fq); phiq_piece<1, 0>(p, fq); phiq_piece<0, 1>(p, fq); phiq_piece<1, 1>(p, fq);
    }
    TS(5);
    uint32_t xr[18];
    {
      const __nv_bfloat16* xp = P.x + (size_t)(r * 128 + warp * 16 + rq) * D_ + 72 * g + 2 * c;
      const __nv_bfloat16 *x40 = xp + (odd ? 0 : 32), *x32 = xp + (odd ? 40 : 0);
#pragma unroll
      for (int j = 0; j < 9; j++) {
        const __nv_bfloat16* q = j < 5 ? x40 + 8 * j : x32 + 8 * (j - 5);
        xr[2 * j] = ldg32(q);
        xr[2 * j + 1] = ldg32(q + 8 * D_);
      }
    }
    const int rw = r * 8 + warp;
    const uint32_t land = A_X + wg * 65536 + wq * 3072;
    {
      float o[44];
      uint64_t d = P.dkvb;
      bar_sync<BAR_KVB, 352>();
      TS(6);
      wg_fence();
      static_for<0, 9>([&](auto s) { wgmma_rs<16, s.value != 0>(o, fq[4 * s.value], fq[4 * s.value + 1], fq[4 * s.value + 2], fq[4 * s.value + 3], d); });
      wg_commit();
      wg_wait<0>(); pin(o);
      bar_arrive<BAR_OMMA, 320>();
      uint32_t f[18], ff[16];
#pragma unroll
      for (int u = 0; u < 2; u++) {
        const float i0 = rcp(o[36 + 2 * u] + 1e-6f), i1 = rcp(o[37 + 2 * u] + 1e-6f), i2 = rcp(o[40 + 2 * u] + 1e-6f), i3 = rcp(o[41 + 2 * u] + 1e-6f);
        const float sc[9] = {i0, i0, c < 1 ? i0 : i1, i1, c < 2 ? i1 : i2, i2, c < 3 ? i2 : i3, i3, i3};
#pragma unroll
        for (int j = 0; j < 9; j++) f[2 * j + u] = pack2(o[4 * j + 2 * u] * sc[j], o[4 * j + 2 * u + 1] * sc[j]);
      }
#pragma unroll
      for (int i = 0; i < 16; i++) ff[i] = odd ? f[i + 2] : f[i];
      stage_piece(land, lane, odd, ff, odd ? f[0] : f[16], odd ? f[1] : f[17]);
      fence_async_smem();
      __syncwarp();
      if (lane == 0) {
        bulk_store(reinterpret_cast<char*>(g_o + rw * 1152) + g * 2304, land, 2304);
        bulk_commit(); bulk_wait_all();
        signal(&g_cnt[(8 + 2 * r + wg) * 32]);
      }
      TS(7);
    }
    {
      float h40[20], h32[16];
      mbar_wait(lb, 1);
      TS(8);
      tail_read(a, g_o + rw * 1152, lane);
      land_read<0>(a, land, lane);                          stage_c<6, 0, 128, 27>(h40, a, o40);
      mbar_wait(lb + 8, 1);  land_read<1>(a, land, lane);   stage_c<6, 6, 128, 28>(h40, a, o40);  wg_wait<1>(); release_c<27>(lane);
      stage_c<12, 0, 64, 29>(h32, a, z);
      mbar_wait(lb + 16, 1); land_read<2>(a, land, lane);   wg_wait<1>(); release_c<28>(lane);
      stage_c<6, 12, 128, 30>(h40, a, o40);
      mbar_wait(lb + 24, 1); land_read<3>(a, land, lane);   wg_wait<1>(); release_c<29>(lane);
      stage_c<6, 18, 128, 31>(h40, a, o40); wg_wait<1>(); release_c<30>(lane);
      stage_c<12, 12, 64, 32>(h32, a, z);
      mbar_wait(lb + 32, 1); land_read<4>(a, land, lane);   wg_wait<1>(); release_c<31>(lane);
      stage_c<6, 24, 128, 33>(h40, a, o40); wg_wait<1>(); release_c<32>(lane);
      stage_c<6, 30, 128, 34>(h40, a, o40); wg_wait<1>(); release_c<33>(lane);
      stage_c<12, 24, 64, 35>(h32, a, z);   wg_wait<1>(); release_c<34>(lane);
      wg_wait<0>(); pin(h40); pin(h32); release_c<35>(lane);
      TS(9);
      uint32_t f[18], ff[16];
      float sl = 0.f, ql = 0.f, sh = 0.f, qh = 0.f;
#pragma unroll
      for (int j = 0; j < 9; j++) {
        const float* v = j < 5 ? &h40[4 * j] : &h32[4 * (j - 5)];
        f[2 * j] = pack2(v[0] + bf_lo(xr[2 * j]), v[1] + bf_hi(xr[2 * j]));
        f[2 * j + 1] = pack2(v[2] + bf_lo(xr[2 * j + 1]), v[3] + bf_hi(xr[2 * j + 1]));
      }
#pragma unroll
      for (int i = 0; i < 8; i++) { ff[i] = odd ? f[i + 2] : f[i + 10]; ff[8 + i] = odd ? f[i + 10] : f[i]; }
      stage_piece(land, lane, odd, ff, odd ? f[0] : f[8], odd ? f[1] : f[9]);
#pragma unroll
      for (int j = 0; j < 9; j++) {
        const float l0 = bf_lo(f[2 * j]), l1 = bf_hi(f[2 * j]), u0 = bf_lo(f[2 * j + 1]), u1 = bf_hi(f[2 * j + 1]);
        sl += l0 + l1; ql = fmaf(l0, l0, fmaf(l1, l1, ql));
        sh += u0 + u1; qh = fmaf(u0, u0, fmaf(u1, u1, qh));
      }
#pragma unroll
      for (int m = 1; m < 4; m <<= 1) {
        sl += __shfl_xor_sync(0xffffffffu, sl, m); ql += __shfl_xor_sync(0xffffffffu, ql, m);
        sh += __shfl_xor_sync(0xffffffffu, sh, m); qh += __shfl_xor_sync(0xffffffffu, qh, m);
      }
      if (c == 0) sts128(land + 2304 + rq * 16, __float_as_uint(sl), __float_as_uint(ql), __float_as_uint(sh), __float_as_uint(qh));
      fence_async_smem();
      __syncwarp();
      if (lane == 0) {
        bulk_store(reinterpret_cast<char*>(g_h + rw * 1152) + g * 2304, land, 2304);
        bulk_store(g_stats + rw * 64 + g * 8, land + 2304, 128);
        bulk_commit(); bulk_wait_all();
        signal(&g_cnt[(40 + 2 * r + wg) * 32]);
      }
      TS(10);
    }
    const uint32_t xw = A_X + warp * 16384;
    {
      float accA[32];
      mbar_wait(lb, 0);
      TS(11);
      tail_read(a, g_h + rw * 1152, lane);
      uint32_t s0, s1, s2, s3, t0, t1, t2, t3;
      const uint32_t sa = A_X + wg * 65536 + 61440 + wq * 1024 + c * 256 + rq * 16;
      lds128(sa, s0, s1, s2, s3);
      lds128(sa + 128, t0, t1, t2, t3);
      land_read<0>(a, land, lane);
      float sl = __uint_as_float(s0) + __uint_as_float(t0), ql = __uint_as_float(s1) + __uint_as_float(t1);
      float sh = __uint_as_float(s2) + __uint_as_float(t2), qh = __uint_as_float(s3) + __uint_as_float(t3);
#pragma unroll
      for (int m = 1; m < 4; m <<= 1) {
        sl += __shfl_xor_sync(0xffffffffu, sl, m); ql += __shfl_xor_sync(0xffffffffu, ql, m);
        sh += __shfl_xor_sync(0xffffffffu, sh, m); qh += __shfl_xor_sync(0xffffffffu, qh, m);
      }
      sl *= (1.f / D_); sh *= (1.f / D_);
      rlo = 0.5f * rsq(fmaxf(ql * (1.f / D_) - sl * sl, 0.f) + 1e-5f);
      rhi = 0.5f * rsq(fmaxf(qh * (1.f / D_) - sh * sh, 0.f) + 1e-5f);
      const uint32_t ml = pack2(sl, sl), mh = pack2(sh, sh);
      auto center = [&](int k0) {
#pragma unroll
        for (int i = 4 * k0; i < 4 * k0 + 24; i++) a[i] = hsub2(a[i], (i & 1) ? mh : ml);
      };
      center(0);                                                       stage_c<6, 0, 128, 36>(accA, a, P.d128);
      mbar_wait(lb + 8, 0);  land_read<1>(a, land, lane); center(6);   stage_c<6, 6, 128, 37>(accA, a, P.d128);
      mbar_wait(lb + 16, 0); land_read<2>(a, land, lane); center(12);  wg_wait<1>(); release_c<36>(lane); stage_c<6, 12, 128, 38>(accA, a, P.d128);
      mbar_wait(lb + 24, 0); land_read<3>(a, land, lane); center(18);  wg_wait<1>(); release_c<37>(lane); stage_c<6, 18, 128, 39>(accA, a, P.d128);
      mbar_wait(lb + 32, 0); land_read<4>(a, land, lane); center(24);  wg_wait<1>(); release_c<38>(lane); stage_c<6, 24, 128, 40>(accA, a, P.d128);
      center(30);                                                      wg_wait<1>(); release_c<39>(lane); stage_c<6, 30, 128, 41>(accA, a, P.d128);
      bar_sync_wg(wg);
      wg_wait<1>(); release_c<40>(lane);
      wg_wait<0>(); pin(accA); release_c<41>(lane);
      park4<0>(accA, xw + lane * 16);
    }
    TS(12);
    const int grow = r * 128 + warp * 16;
    {
      float acc[64];
      uint32_t t8 = 42 * 8;
#pragma unroll 1
      for (int i = 0; i < 8; i++) {
        const uint32_t b1a = A_B1 + c * 16 + i * 512 - 256;
        const uint32_t g0 = xw + lane * 16 + ((i * 4096 - 2048) & 16383), g1 = xw + lane * 16 + ((i * 4096) & 16383);
        static_for<0, 12>([&](auto ss) {
          constexpr int st = ss.value;
          stage_r<3 * st>(acc, a, t8 + 8 * st, P.d128w);
          if constexpr (st < 4) { if (i > 0 && i <= 4) gelu_chunk(g0 + st * 512, b1a + st * 64, rlo, rhi); }
          else if constexpr (st < 8) { if (i <= 4) gelu_chunk(g1 + (st - 4) * 512, b1a + st * 64, rlo, rhi); }
          else if constexpr (st == 8) {
            if (i == 4) {
#pragma unroll
              for (int u = 28; u < 36; u++) lds128(xw + lane * 16 + (u & 31) * 512, a[4 * u], a[4 * u + 1], a[4 * u + 2], a[4 * u + 3]);
              mbar_wait(A_OUTRDY, 0);
              fence_async_global();
              TS(14);
            }
          }
          if constexpr (st > 0) { wg_wait<1>(); release_r(t8 + 8 * st - 8, lane); }
        });
        wg_wait<0>(); pin(acc); release_r(t8 + 88, lane);
        if (i < 4) {
          if (i == 3) {
            TS(13);
#pragma unroll
            for (int u = 0; u < 28; u++) lds128(xw + lane * 16 + u * 512, a[4 * u], a[4 * u + 1], a[4 * u + 2], a[4 * u + 3]);
          }
          park4<0>(acc, g1 + 2048);
          park4<4>(acc, xw + lane * 16 + ((i * 4096 + 4096) & 16383));
        } else {
          const uint32_t st = xw + (i & 3) * 4096;
          __syncwarp();
          out_stage<0>(acc, st, lane);
          out_stage<4>(acc, st + 2048, lane);
          fence_async_smem();
          __syncwarp();
          if (lane == 0) { out_send(&P.tout, st, 128 * i - 512, grow); out_send(&P.tout, st + 2048, 128 * i - 448, grow); bulk_commit(); }
        }
        t8 += 96;
      }
    }
    {
      float acc[32];
      stage_c<6, 0, 128, 138>(acc, a, P.d128);
      stage_c<6, 6, 128, 139>(acc, a, P.d128);
      stage_c<6, 12, 128, 140>(acc, a, P.d128);
      stage_c<6, 18, 128, 141>(acc, a, P.d128);
      stage_c<6, 24, 128, 142>(acc, a, P.d128);
      stage_c<6, 30, 128, 143>(acc, a, P.d128);
      if (lane == 0) asm volatile("cp.async.bulk.wait_group.read 3;" ::: "memory");
      __syncwarp();
      wg_wait<0>(); pin(acc);
      TS(15);
      out_stage<0>(acc, xw, lane);
      fence_async_smem();
      __syncwarp();
      if (lane == 0) { out_send(&P.tout, xw, 512, grow); bulk_commit(); bulk_wait_all(); }
      TS(16);
      TSG(31);
      TS_DUMP();
    }
  }
}

typedef CUresult (*EncodeFn)(CUtensorMap*, CUtensorMapDataType, cuuint32_t, void*, const cuuint64_t*, const cuuint64_t*, const cuuint32_t*,
                             const cuuint32_t*, CUtensorMapInterleave, CUtensorMapSwizzle, CUtensorMapL2promotion, CUtensorMapFloatOOBfill);

void enc2d(EncodeFn fn, CUtensorMap* m, const void* base, uint64_t cols, uint64_t rows, uint32_t bc, uint32_t br) {
  cuuint64_t gd[2] = {cols, rows}, gs[1] = {cols * 2};
  cuuint32_t bd[2] = {bc, br}, es[2] = {1, 1};
  fn(m, CU_TENSOR_MAP_DATA_TYPE_BFLOAT16, 2, const_cast<void*>(base), gd, gs, bd, es, CU_TENSOR_MAP_INTERLEAVE_NONE,
     bc == 64 ? CU_TENSOR_MAP_SWIZZLE_128B : CU_TENSOR_MAP_SWIZZLE_64B, CU_TENSOR_MAP_L2_PROMOTION_L2_128B, CU_TENSOR_MAP_FLOAT_OOB_FILL_NONE);
}

}

extern "C" void kernel_launch(void* const* d_in, const int* in_sizes, int n_in, void* d_out, int out_size) {
  (void)in_sizes; (void)n_in; (void)out_size;
  static EncodeFn fn = nullptr;
  static void *po = nullptr, *ph = nullptr;
  if (!fn) {
    void* p = nullptr;
    cudaDriverEntryPointQueryResult q;
    cudaGetDriverEntryPoint("cuTensorMapEncodeTiled", &p, cudaEnableDefault, &q);
    fn = (EncodeFn)p;
    cudaFuncSetAttribute(fused_block_kernel, cudaFuncAttributeMaxDynamicSharedMemorySize, SMEM_BYTES);
    cudaGetSymbolAddress(&po, g_o);
    cudaGetSymbolAddress(&ph, g_h);
  }
  Params P;
  P.x = (const __nv_bfloat16*)d_in[0];
  P.wqkv = (const __nv_bfloat16*)d_in[1];
  P.wphi = (const __nv_bfloat16*)d_in[2];
  P.wo = (const __nv_bfloat16*)d_in[3];
  P.w1 = (const __nv_bfloat16*)d_in[5];
  P.b1 = (const __nv_bfloat16*)d_in[6];
  P.w2 = (const __nv_bfloat16*)d_in[7];
  P.b2 = (const __nv_bfloat16*)d_in[8];
  P.out = (__nv_bfloat16*)d_out;
  P.d128 = desc64(SB, 16, 1024, 1);
  P.d128w = desc64(SB, 6144, 1024, 1);
  P.d64 = desc64(SB, 16, 512, 2);
  P.dwphi = desc64(A_WPHI, 128, 1280, 0);
  P.dkvb = desc64(A_KVB, 128, 2304, 0);
  P.dphi = desc64(A_PHI, 16, 1024, 1);
  P.dv = desc64(A_V, 128, 2048, 0);
  enc2d(fn, &P.tq64, P.wqkv, 3 * D_, D_, 64, 96);
  enc2d(fn, &P.tq32, P.wqkv, 3 * D_, D_, 32, 192);
  enc2d(fn, &P.to64, P.wo, D_, D_, 64, 96);
  enc2d(fn, &P.to32, P.wo, D_, D_, 32, 192);
  enc2d(fn, &P.tw1, P.w1, F_, D_, 64, 96);
  enc2d(fn, &P.tw2, P.w2, D_, F_, 64, 96);
  enc2d(fn, &P.tout, P.out, D_, S_, 64, 16);
  for (int i = 0; i < 2; i++) {
    const cuuint64_t cols = i ? D_ : F_, rows = i ? F_ : D_;
    cuuint64_t gd[3] = {64, rows, cols / 64}, gs[2] = {cols * 2, 128};
    cuuint32_t bd[3] = {64, 48, 2}, es[3] = {1, 1, 1};
    fn(i ? &P.tw2b : &P.tw1b, CU_TENSOR_MAP_DATA_TYPE_BFLOAT16, 3, const_cast<__nv_bfloat16*>(i ? P.w2 : P.w1), gd, gs, bd, es, CU_TENSOR_MAP_INTERLEAVE_NONE,
       CU_TENSOR_MAP_SWIZZLE_128B, CU_TENSOR_MAP_L2_PROMOTION_L2_128B, CU_TENSOR_MAP_FLOAT_OOB_FILL_NONE);
  }
  {
    cuuint64_t gd[3] = {64, (cuuint64_t)S_, 9}, gs[2] = {D_ * 2, 128};
    cuuint32_t bd[3] = {64, 64, 3}, es[3] = {1, 1, 1};
    fn(&P.tx, CU_TENSOR_MAP_DATA_TYPE_BFLOAT16, 3, const_cast<__nv_bfloat16*>(P.x), gd, gs, bd, es, CU_TENSOR_MAP_INTERLEAVE_NONE,
       CU_TENSOR_MAP_SWIZZLE_128B, CU_TENSOR_MAP_L2_PROMOTION_L2_128B, CU_TENSOR_MAP_FLOAT_OOB_FILL_NONE);
  }
  for (int i = 0; i < 2; i++) {
    cuuint64_t gd[3] = {256, 18, 128}, gs[2] = {1024, 18432};
    cuuint32_t bd[3] = {256, 3, 4}, es[3] = {1, 1, 1};
    fn(i ? &P.tgh : &P.tgo, CU_TENSOR_MAP_DATA_TYPE_UINT32, 3, i ? ph : po, gd, gs, bd, es, CU_TENSOR_MAP_INTERLEAVE_NONE,
       CU_TENSOR_MAP_SWIZZLE_NONE, CU_TENSOR_MAP_L2_PROMOTION_L2_128B, CU_TENSOR_MAP_FLOAT_OOB_FILL_NONE);
  }
  fused_block_kernel<<<128, 384, SMEM_BYTES>>>(P);
}
```

```cpp
#include <cuda_runtime.h>
#include <cuda.h>
#include <cuda_bf16.h>
#include <stdint.h>
#include <type_traits>

namespace {

constexpr int S_ = 2048, D_ = 576, F_ = 4608;
constexpr int NSLOT = 8, SLOT_BYTES = 12288;
constexpr uint32_t SB       = 1024;
constexpr uint32_t A_X      = SB + NSLOT * SLOT_BYTES;
constexpr uint32_t A_E      = A_X + 102400;
constexpr uint32_t A_PHI    = A_X;
constexpr uint32_t A_V      = A_X + 65536;
constexpr uint32_t A_WPHI   = A_X + 90112;
constexpr uint32_t A_KVB    = A_X + 101632;
constexpr uint32_t A_B1     = A_X + 131072;
constexpr uint32_t A_FULL   = A_B1 + 2304;
constexpr uint32_t A_EFULL  = A_FULL + 64;
constexpr uint32_t A_XC     = A_FULL + 80;
constexpr uint32_t A_EMPTY  = A_FULL + 128;
constexpr uint32_t A_EEMPTY = A_EMPTY + 64;
constexpr uint32_t A_LAND   = A_EMPTY + 80;
constexpr uint32_t A_PREP   = A_LAND + 80;
constexpr uint32_t A_XR     = A_PREP + 24;
constexpr uint32_t A_OUTRDY = A_XR + 8;
constexpr uint32_t A_KVRDY  = A_OUTRDY + 8;
constexpr uint32_t A_VTAB   = A_B1 + 1536;
constexpr uint32_t A_TGT    = A_VTAB + 192;
constexpr uint32_t A_DUMMY  = A_TGT + 4;
constexpr uint32_t SMEM_BYTES = A_KVRDY + 8 - SB;
static_assert((A_FULL & 63) == 0, "barrier block alignment");
constexpr int SPIN_LIMIT = 1 << 20;

enum { BAR_INIT = 1, BAR_T0 = 2, BAR_T1 = 3, BAR_KVOUT = 4, BAR_KVIN = 5, BAR_HELP = 6, BAR_WG = 7  , BAR_OMMA = 9, BAR_T2 = 10, BAR_HDONE = 11 };

constexpr int ST_WO = 21, ST_FFN = 28;
__host__ __device__ constexpr bool     st_extra(uint32_t n) { return n == 8 || n == 9; }
__host__ __device__ constexpr uint32_t st_virt(uint32_t n) { return n < 10 ? n : n - 2; }
__host__ __device__ constexpr uint32_t st_addr(uint32_t n) { return st_extra(n) ? A_E + (n & 1) * SLOT_BYTES : SB + (st_virt(n) & 7) * SLOT_BYTES; }
__host__ __device__ constexpr uint32_t st_full(uint32_t n) { return st_extra(n) ? A_EFULL + (n & 1) * 8 : A_FULL + (st_virt(n) & 7) * 8; }
__host__ __device__ constexpr uint32_t st_empty(uint32_t n) { return st_extra(n) ? A_EEMPTY + (n & 1) * 8 : A_EMPTY + (st_virt(n) & 7) * 8; }
__host__ __device__ constexpr uint32_t st_par(uint32_t n) { return st_extra(n) ? 0 : (st_virt(n) >> 3) & 1; }
__host__ __device__ constexpr uint32_t x_block(int b) { return b == 0 ? A_X - 16384 : b < 3 ? A_X + 81920 + b * 16384 : b == 3 ? A_X + 81920 : A_X + (b - 4) * 16384; }

struct Params {
  CUtensorMap tx, tq64, tq8, to64, to8, tw1, tw2, tout, tgx, txr;
  const __nv_bfloat16 *x, *wqkv, *wphi, *wo, *w1, *b1, *w2, *b2;
  __nv_bfloat16* out;
  uint64_t dq[5], d8o, dwphi2;
  uint64_t d128, dba, dbb, d8, dwphi, dkvb, dphi, dv;
};

__device__ uint4    g_x[2 * 128 * 36 * 32];
#define g_o g_x
#define g_h (g_x + 128 * 36 * 32)
__device__ float4   g_stats[128 * 64];
__device__ float4   g_kv[8 * 864];
__device__ unsigned g_cnt[(8 + 32 + 32 + 16) * 32];
__device__ unsigned g_epoch[128];

__device__ __forceinline__ void mbar_init(uint32_t bar, uint32_t cnt) { asm volatile("mbarrier.init.shared::cta.b64 [%0], %1;" ::"r"(bar), "r"(cnt)); }
__device__ __forceinline__ void mbar_arrive(uint32_t bar) { asm volatile("mbarrier.arrive.shared::cta.b64 _, [%0];" ::"r"(bar) : "memory"); }
__device__ __forceinline__ void mbar_wait(uint32_t bar, uint32_t parity) {
  asm volatile(
      "{\n.reg .pred p;\n"
      "WAIT_%=:\n"
      "mbarrier.try_wait.parity.shared::cta.b64 p, [%0], %1;\n"
      "@p bra DONE_%=;\n"
      "bra WAIT_%=;\n"
      "DONE_%=:\n}\n" ::"r"(bar), "r"(parity) : "memory");
}
__device__ __forceinline__ void sched_fence() {
  asm volatile("{\n.reg .u32 t;\nmov.u32 t, %%clock;\nst.shared.b32 [%0], t;\n}\n" ::"r"(A_DUMMY) : "memory");
}
template <int ID, int N> __device__ __forceinline__ void bar_sync() { asm volatile("bar.sync %0, %1;" ::"n"(ID), "n"(N) : "memory"); }
template <int ID, int N> __device__ __forceinline__ void bar_arrive() { asm volatile("bar.arrive %0, %1;" ::"n"(ID), "n"(N) : "memory"); }
__device__ __forceinline__ void bar_sync_wg(int wg) { asm volatile("bar.sync %0, 128;" ::"r"(BAR_WG + wg) : "memory"); }
__device__ __forceinline__ void fence_async_smem() { asm volatile("fence.proxy.async.shared::cta;" ::: "memory"); }
__device__ __forceinline__ void fence_async_global() { asm volatile("fence.proxy.async.global;" ::: "memory"); }
__device__ __forceinline__ void tma2d_e(uint32_t dst, const CUtensorMap* m, int c0, int c1, uint32_t bar, uint32_t bytes) {
  asm volatile("{\n.reg .pred p;\nelect.sync _|p, 0xffffffff;\n@p mbarrier.arrive.expect_tx.shared::cta.b64 _, [%2], %5;\n"
               "@p cp.async.bulk.tensor.2d.shared::cluster.global.mbarrier::complete_tx::bytes [%0], [%1, {%3, %4}], [%2];\n}\n"
               ::"r"(dst), "l"(m), "r"(bar), "r"(c0), "r"(c1), "r"(bytes) : "memory");
}
__device__ __forceinline__ void tma3d_e(uint32_t dst, const CUtensorMap* m, int c0, int c1, int c2, uint32_t bar, uint32_t bytes) {
  asm volatile("{\n.reg .pred p;\nelect.sync _|p, 0xffffffff;\n@p mbarrier.arrive.expect_tx.shared::cta.b64 _, [%2], %5;\n"
               "@p cp.async.bulk.tensor.3d.shared::cluster.global.mbarrier::complete_tx::bytes [%0], [%1, {%6, %3, %4}], [%2];\n}\n"
               ::"r"(dst), "l"(m), "r"(bar), "r"(c1), "r"(c2), "r"(bytes), "r"(c0) : "memory");
}
__device__ __forceinline__ bool elect() {
  uint32_t e;
  asm volatile("{\n.reg .pred p;\nelect.sync _|p, 0xffffffff;\nselp.u32 %0, 1, 0, p;\n}\n" : "=r"(e));
  return e;
}
__device__ __forceinline__ void bulk_store(void* dst, uint32_t src, uint32_t bytes) {
  asm volatile("cp.async.bulk.global.shared::cta.bulk_group [%0], [%1], %2;" ::"l"(dst), "r"(src), "r"(bytes) : "memory");
}
__device__ __forceinline__ void bulk_commit() { asm volatile("cp.async.bulk.commit_group;" ::: "memory"); }
__device__ __forceinline__ void bulk_wait_all() { asm volatile("cp.async.bulk.wait_group 0;" ::: "memory"); }
__device__ __forceinline__ void l2_prefetch(const void* p, uint32_t bytes) { asm volatile("cp.async.bulk.prefetch.L2.global [%0], %1;" ::"l"(p), "r"(bytes) : "memory"); }
__device__ __forceinline__ void wg_fence() { asm volatile("wgmma.fence.sync.aligned;" ::: "memory"); }
__device__ __forceinline__ void wg_commit() { asm volatile("wgmma.commit_group.sync.aligned;" ::: "memory"); }
template <int N> __device__ __forceinline__ void wg_wait() { asm volatile("wgmma.wait_group.sync.aligned %0;" ::"n"(N) : "memory"); }
template <int N> __device__ __forceinline__ void pin(float (&d)[N]) {
#pragma unroll
  for (int i = 0; i < N; i++) asm volatile("" : "+f"(d[i])::"memory");
}
__device__ __forceinline__ uint32_t pack2(float lo, float hi) { uint32_t r; asm("cvt.rn.bf16x2.f32 %0, %1, %2;" : "=r"(r) : "f"(hi), "f"(lo)); return r; }
__device__ __forceinline__ float bf_lo(uint32_t v) { return __uint_as_float(v << 16); }
__device__ __forceinline__ float bf_hi(uint32_t v) { return __uint_as_float(v & 0xffff0000u); }
__device__ __forceinline__ uint32_t hfma2(uint32_t a, uint32_t b, uint32_t c) { uint32_t r; asm("fma.rn.bf16x2 %0, %1, %2, %3;" : "=r"(r) : "r"(a), "r"(b), "r"(c)); return r; }
__device__ __forceinline__ uint32_t hadd2(uint32_t a, uint32_t b) { uint32_t r; asm("add.rn.bf16x2 %0, %1, %2;" : "=r"(r) : "r"(a), "r"(b)); return r; }
__device__ __forceinline__ float ex2(float x) { float r; asm("ex2.approx.ftz.f32 %0, %1;" : "=f"(r) : "f"(x)); return r; }
__device__ __forceinline__ float rcp(float x) { float r; asm("rcp.approx.ftz.f32 %0, %1;" : "=f"(r) : "f"(x)); return r; }
__device__ __forceinline__ float rsq(float x) { float r; asm("rsqrt.approx.ftz.f32 %0, %1;" : "=f"(r) : "f"(x)); return r; }
__device__ __forceinline__ float tanh_(float x) { float r; asm("tanh.approx.f32 %0, %1;" : "=f"(r) : "f"(x)); return r; }
__device__ __forceinline__ void mma16816(float (&d)[4], uint32_t a0, uint32_t a1, uint32_t a2, uint32_t a3, uint32_t b0, uint32_t b1) {
  asm("mma.sync.aligned.m16n8k16.row.col.f32.bf16.bf16.f32 {%0,%1,%2,%3}, {%4,%5,%6,%7}, {%8,%9}, {%0,%1,%2,%3};"
      : "+f"(d[0]), "+f"(d[1]), "+f"(d[2]), "+f"(d[3]) : "r"(a0), "r"(a1), "r"(a2), "r"(a3), "r"(b0), "r"(b1));
}
__device__ __forceinline__ void mma1688(float (&d)[4], uint32_t a0, uint32_t a1, uint32_t b0) {
  asm("mma.sync.aligned.m16n8k8.row.col.f32.bf16.bf16.f32 {%0,%1,%2,%3}, {%4,%5}, {%6}, {%0,%1,%2,%3};"
      : "+f"(d[0]), "+f"(d[1]), "+f"(d[2]), "+f"(d[3]) : "r"(a0), "r"(a1), "r"(b0));
}
__device__ __forceinline__ void sts32(uint32_t a, uint32_t v) { asm volatile("st.shared.b32 [%0], %1;" ::"r"(a), "r"(v) : "memory"); }
__device__ __forceinline__ void sts64(uint32_t a, uint32_t v0, uint32_t v1) { asm volatile("st.shared.v2.b32 [%0], {%1,%2};" ::"r"(a), "r"(v0), "r"(v1) : "memory"); }
__device__ __forceinline__ void sts128(uint32_t a, uint32_t v0, uint32_t v1, uint32_t v2, uint32_t v3) { asm volatile("st.shared.v4.b32 [%0], {%1,%2,%3,%4};" ::"r"(a), "r"(v0), "r"(v1), "r"(v2), "r"(v3) : "memory"); }
__device__ __forceinline__ void lds64(uint32_t a, uint32_t& v0, uint32_t& v1) { asm volatile("ld.shared.v2.b32 {%0,%1}, [%2];" : "=r"(v0), "=r"(v1) : "r"(a) : "memory"); }
__device__ __forceinline__ void lds128(uint32_t a, uint32_t& v0, uint32_t& v1, uint32_t& v2, uint32_t& v3) { asm volatile("ld.shared.v4.b32 {%0,%1,%2,%3}, [%4];" : "=r"(v0), "=r"(v1), "=r"(v2), "=r"(v3) : "r"(a) : "memory"); }
__device__ __forceinline__ void ldsm4(uint32_t a, uint32_t& v0, uint32_t& v1, uint32_t& v2, uint32_t& v3) { asm volatile("ldmatrix.sync.aligned.m8n8.x4.shared.b16 {%0,%1,%2,%3}, [%4];" : "=r"(v0), "=r"(v1), "=r"(v2), "=r"(v3) : "r"(a) : "memory"); }
__device__ __forceinline__ void ldg128(const void* p, uint32_t& v0, uint32_t& v1, uint32_t& v2, uint32_t& v3) { asm volatile("ld.relaxed.gpu.global.v4.b32 {%0,%1,%2,%3}, [%4];" : "=r"(v0), "=r"(v1), "=r"(v2), "=r"(v3) : "l"(p) : "memory"); }
__device__ __forceinline__ void ldg64(const void* p, uint32_t& v0, uint32_t& v1) { asm volatile("ld.relaxed.gpu.global.v2.b32 {%0,%1}, [%2];" : "=r"(v0), "=r"(v1) : "l"(p) : "memory"); }
__device__ __forceinline__ uint32_t ldg32(const void* p) { uint32_t v; asm volatile("ld.global.b32 %0, [%1];" : "=r"(v) : "l"(p) : "memory"); return v; }
__device__ __forceinline__ void stg32(void* p, uint32_t v) { asm volatile("st.global.b32 [%0], %1;" ::"l"(p), "r"(v) : "memory"); }
__device__ __forceinline__ void signal(unsigned* c) { asm volatile("red.relaxed.gpu.global.add.u32 [%0], 1;" ::"l"(c) : "memory"); }
__device__ __forceinline__ void signal_release(unsigned* c) { asm volatile("red.release.gpu.global.add.u32 [%0], 1;" ::"l"(c) : "memory"); }
__device__ __forceinline__ uint32_t poll(const unsigned* c, unsigned target) {
  unsigned v; int n = 0;
  do { asm volatile("ld.relaxed.gpu.global.u32 %0, [%1];" : "=r"(v) : "l"(c) : "memory"); } while ((int)(v - target) < 0 && ++n < SPIN_LIMIT);
  return n < SPIN_LIMIT;
}

template <int INC, int SCALE_D>
__device__ __forceinline__ void wgmma_rs(float (&d)[4], uint32_t a0, uint32_t a1, uint32_t a2, uint32_t a3, uint64_t& bd) {
  asm volatile("{\n.reg .pred p;\nsetp.ne.b32 p, %10, 0;\n"
    "wgmma.mma_async.sync.aligned.m64n8k16.f32.bf16.bf16 {%0, %1, %2, %3}, {%5, %6, %7, %8}, %4, p, 1, 1, 1;\n"
    "add.s64 %4, %4, %9;\n}\n"
    : "+f"(d[0]), "+f"(d[1]), "+f"(d[2]), "+f"(d[3]), "+l"(bd)
    : "r"(a0), "r"(a1), "r"(a2), "r"(a3), "n"(INC), "n"(SCALE_D));
}
template <int INC, int SCALE_D>
__device__ __forceinline__ void wgmma_rs(float (&d)[12], uint32_t a0, uint32_t a1, uint32_t a2, uint32_t a3, uint64_t& bd) {
  asm volatile("{\n.reg .pred p;\nsetp.ne.b32 p, %18, 0;\n"
    "wgmma.mma_async.sync.aligned.m64n24k16.f32.bf16.bf16 {%0, %1, %2, %3, %4, %5, %6, %7, %8, %9, %10, %11}, {%13, %14, %15, %16}, %12, p, 1, 1, 1;\n"
    "add.s64 %12, %12, %17;\n}\n"
    : "+f"(d[0]), "+f"(d[1]), "+f"(d[2]), "+f"(d[3]), "+f"(d[4]), "+f"(d[5]), "+f"(d[6]), "+f"(d[7]), "+f"(d[8]), "+f"(d[9]), "+f"(d[10]), "+f"(d[11]), "+l"(bd)
    : "r"(a0), "r"(a1), "r"(a2), "r"(a3), "n"(INC), "n"(SCALE_D));
}
template <int INC, int SCALE_D>
__device__ __forceinline__ void wgmma_rs(float (&d)[32], uint32_t a0, uint32_t a1, uint32_t a2, uint32_t a3, uint64_t& bd) {
  asm volatile("{\n.reg .pred p;\nsetp.ne.b32 p, %38, 0;\n"
    "wgmma.mma_async.sync.aligned.m64n64k16.f32.bf16.bf16 {%0, %1, %2, %3, %4, %5, %6, %7, %8, %9, %10, %11, %12, %13, %14, %15, %16, %17, %18, %19, %20, %21, %22, %23, %24, %25, %26, %27, %28, %29, %30, %31}, {%33, %34, %35, %36}, %32, p, 1, 1, 1;\n"
    "add.s64 %32, %32, %37;\n}\n"
    : "+f"(d[0]), "+f"(d[1]), "+f"(d[2]), "+f"(d[3]), "+f"(d[4]), "+f"(d[5]), "+f"(d[6]), "+f"(d[7]), "+f"(d[8]), "+f"(d[9]), "+f"(d[10]), "+f"(d[11]), "+f"(d[12]), "+f"(d[13]), "+f"(d[14]), "+f"(d[15]), "+f"(d[16]), "+f"(d[17]), "+f"(d[18]), "+f"(d[19]), "+f"(d[20]), "+f"(d[21]), "+f"(d[22]), "+f"(d[23]), "+f"(d[24]), "+f"(d[25]), "+f"(d[26]), "+f"(d[27]), "+f"(d[28]), "+f"(d[29]), "+f"(d[30]), "+f"(d[31]), "+l"(bd)
    : "r"(a0), "r"(a1), "r"(a2), "r"(a3), "n"(INC), "n"(SCALE_D));
}
template <int INC, int SCALE_D>
__device__ __forceinline__ void wgmma_rs(float (&d)[36], uint32_t a0, uint32_t a1, uint32_t a2, uint32_t a3, uint64_t& bd) {
  asm volatile("{\n.reg .pred p;\nsetp.ne.b32 p, %42, 0;\n"
    "wgmma.mma_async.sync.aligned.m64n72k16.f32.bf16.bf16 {%0, %1, %2, %3, %4, %5, %6, %7, %8, %9, %10, %11, %12, %13, %14, %15, %16, %17, %18, %19, %20, %21, %22, %23, %24, %25, %26, %27, %28, %29, %30, %31, %32, %33, %34, %35}, {%37, %38, %39, %40}, %36, p, 1, 1, 1;\n"
    "add.s64 %36, %36, %41;\n}\n"
    : "+f"(d[0]), "+f"(d[1]), "+f"(d[2]), "+f"(d[3]), "+f"(d[4]), "+f"(d[5]), "+f"(d[6]), "+f"(d[7]), "+f"(d[8]), "+f"(d[9]), "+f"(d[10]), "+f"(d[11]), "+f"(d[12]), "+f"(d[13]), "+f"(d[14]), "+f"(d[15]), "+f"(d[16]), "+f"(d[17]), "+f"(d[18]), "+f"(d[19]), "+f"(d[20]), "+f"(d[21]), "+f"(d[22]), "+f"(d[23]), "+f"(d[24]), "+f"(d[25]), "+f"(d[26]), "+f"(d[27]), "+f"(d[28]), "+f"(d[29]), "+f"(d[30]), "+f"(d[31]), "+f"(d[32]), "+f"(d[33]), "+f"(d[34]), "+f"(d[35]), "+l"(bd)
    : "r"(a0), "r"(a1), "r"(a2), "r"(a3), "n"(INC), "n"(SCALE_D));
}
template <int INC, int SCALE_D>
__device__ __forceinline__ void wgmma_rs(float (&d)[44], uint32_t a0, uint32_t a1, uint32_t a2, uint32_t a3, uint64_t& bd) {
  asm volatile("{\n.reg .pred p;\nsetp.ne.b32 p, %50, 0;\n"
    "wgmma.mma_async.sync.aligned.m64n88k16.f32.bf16.bf16 {%0, %1, %2, %3, %4, %5, %6, %7, %8, %9, %10, %11, %12, %13, %14, %15, %16, %17, %18, %19, %20, %21, %22, %23, %24, %25, %26, %27, %28, %29, %30, %31, %32, %33, %34, %35, %36, %37, %38, %39, %40, %41, %42, %43}, {%45, %46, %47, %48}, %44, p, 1, 1, 1;\n"
    "add.s64 %44, %44, %49;\n}\n"
    : "+f"(d[0]), "+f"(d[1]), "+f"(d[2]), "+f"(d[3]), "+f"(d[4]), "+f"(d[5]), "+f"(d[6]), "+f"(d[7]), "+f"(d[8]), "+f"(d[9]), "+f"(d[10]), "+f"(d[11]), "+f"(d[12]), "+f"(d[13]), "+f"(d[14]), "+f"(d[15]), "+f"(d[16]), "+f"(d[17]), "+f"(d[18]), "+f"(d[19]), "+f"(d[20]), "+f"(d[21]), "+f"(d[22]), "+f"(d[23]), "+f"(d[24]), "+f"(d[25]), "+f"(d[26]), "+f"(d[27]), "+f"(d[28]), "+f"(d[29]), "+f"(d[30]), "+f"(d[31]), "+f"(d[32]), "+f"(d[33]), "+f"(d[34]), "+f"(d[35]), "+f"(d[36]), "+f"(d[37]), "+f"(d[38]), "+f"(d[39]), "+f"(d[40]), "+f"(d[41]), "+f"(d[42]), "+f"(d[43]), "+l"(bd)
    : "r"(a0), "r"(a1), "r"(a2), "r"(a3), "n"(INC), "n"(SCALE_D));
}
template <int INC>
__device__ __forceinline__ void wgmma_rp(float (&d)[32], uint32_t a0, uint32_t a1, uint32_t a2, uint32_t a3, uint64_t& bd, int scale_d) {
  asm volatile("{\n.reg .pred p;\nsetp.ne.b32 p, %38, 0;\n"
    "wgmma.mma_async.sync.aligned.m64n64k16.f32.bf16.bf16 {%0, %1, %2, %3, %4, %5, %6, %7, %8, %9, %10, %11, %12, %13, %14, %15, %16, %17, %18, %19, %20, %21, %22, %23, %24, %25, %26, %27, %28, %29, %30, %31}, {%33, %34, %35, %36}, %32, p, 1, 1, 1;\n"
    "add.s64 %32, %32, %37;\n}\n"
    : "+f"(d[0]), "+f"(d[1]), "+f"(d[2]), "+f"(d[3]), "+f"(d[4]), "+f"(d[5]), "+f"(d[6]), "+f"(d[7]), "+f"(d[8]), "+f"(d[9]), "+f"(d[10]), "+f"(d[11]), "+f"(d[12]), "+f"(d[13]), "+f"(d[14]), "+f"(d[15]), "+f"(d[16]), "+f"(d[17]), "+f"(d[18]), "+f"(d[19]), "+f"(d[20]), "+f"(d[21]), "+f"(d[22]), "+f"(d[23]), "+f"(d[24]), "+f"(d[25]), "+f"(d[26]), "+f"(d[27]), "+f"(d[28]), "+f"(d[29]), "+f"(d[30]), "+f"(d[31]), "+l"(bd)
    : "r"(a0), "r"(a1), "r"(a2), "r"(a3), "n"(INC), "r"(scale_d));
}
__device__ __forceinline__ void wgmma_init(float (&d)[32], uint64_t ad, uint64_t bd) {
  asm volatile("{\n.reg .pred p;\nsetp.ne.b32 p, 0, 0;\n"
    "wgmma.mma_async.sync.aligned.m64n64k16.f32.bf16.bf16 {%0, %1, %2, %3, %4, %5, %6, %7, %8, %9, %10, %11, %12, %13, %14, %15, %16, %17, %18, %19, %20, %21, %22, %23, %24, %25, %26, %27, %28, %29, %30, %31}, %32, %33, p, 1, 1, 0, 1;\n}\n"
    : "+f"(d[0]), "+f"(d[1]), "+f"(d[2]), "+f"(d[3]), "+f"(d[4]), "+f"(d[5]), "+f"(d[6]), "+f"(d[7]), "+f"(d[8]), "+f"(d[9]), "+f"(d[10]), "+f"(d[11]), "+f"(d[12]), "+f"(d[13]), "+f"(d[14]), "+f"(d[15]), "+f"(d[16]), "+f"(d[17]), "+f"(d[18]), "+f"(d[19]), "+f"(d[20]), "+f"(d[21]), "+f"(d[22]), "+f"(d[23]), "+f"(d[24]), "+f"(d[25]), "+f"(d[26]), "+f"(d[27]), "+f"(d[28]), "+f"(d[29]), "+f"(d[30]), "+f"(d[31])
    : "l"(ad), "l"(bd));
}
template <int INCA, int INCB, int SCALE_D>
__device__ __forceinline__ void wgmma_ss_tt(float (&d)[12], uint64_t& ad, uint64_t& bd) {
  asm volatile("{\n.reg .pred p;\nsetp.ne.b32 p, %16, 0;\n"
    "wgmma.mma_async.sync.aligned.m64n24k16.f32.bf16.bf16 {%0, %1, %2, %3, %4, %5, %6, %7, %8, %9, %10, %11}, %12, %13, p, 1, 1, 1, 1;\n"
    "add.s64 %12, %12, %14;\nadd.s64 %13, %13, %15;\n}\n"
    : "+f"(d[0]), "+f"(d[1]), "+f"(d[2]), "+f"(d[3]), "+f"(d[4]), "+f"(d[5]), "+f"(d[6]), "+f"(d[7]), "+f"(d[8]), "+f"(d[9]), "+f"(d[10]), "+f"(d[11]), "+l"(ad), "+l"(bd)
    : "n"(INCA), "n"(INCB), "n"(SCALE_D));
}

__host__ __device__ constexpr uint32_t desc_lo(uint32_t addr, uint32_t lbo) { return ((addr & 0x3FFFF) >> 4) | ((lbo >> 4) << 16); }
__host__ __device__ constexpr uint32_t desc_hi(uint32_t sbo, uint32_t swz) { return (sbo >> 4) | (swz << 30); }
__host__ __device__ constexpr uint64_t desc64(uint32_t addr, uint32_t lbo, uint32_t sbo, uint32_t swz) { return ((uint64_t)desc_hi(sbo, swz) << 32) | desc_lo(addr, lbo); }
template <uint32_t OFF> __device__ __forceinline__ uint64_t dadd(uint64_t base) {
  uint64_t d;
  asm volatile("add.s64 %0, %1, %2;" : "=l"(d) : "l"(base), "n"(OFF));
  return d;
}
template <int I> using ic = std::integral_constant<int, I>;
template <int I, int N, class F> __device__ __forceinline__ void static_for(F f) {
  if constexpr (I < N) { f(std::integral_constant<int, I>{}); static_for<I + 1, N>(f); }
}

template <int KS, int K0, int INC, int ACC, int NA>
__device__ __forceinline__ void mma_run(float (&acc)[NA], const uint32_t (&a)[144], uint64_t d) {
  static_for<0, KS>([&](auto kk) {
    constexpr int k = K0 + kk.value;
    wgmma_rs<INC, (k != 0 || ACC)>(acc, a[4 * k], a[4 * k + 1], a[4 * k + 2], a[4 * k + 3], d);
  });
}
template <int KS, int K0, int INC, int ACC, int NA>
__device__ __forceinline__ void stage_issue(float (&acc)[NA], const uint32_t (&a)[144], uint64_t d) {
  wg_fence();
  mma_run<KS, K0, INC, ACC>(acc, a, d);
  wg_commit();
}
template <int KS, int K0, int INC, int IT, int ACC = 0, int NA>
__device__ __forceinline__ void stage_c(float (&acc)[NA], const uint32_t (&a)[144], uint64_t base) {
  mbar_wait(st_full(IT), st_par(IT));
  stage_issue<KS, K0, INC, ACC>(acc, a, dadd<(st_addr(IT) - SB) / 16>(base));
}
template <int IT> __device__ __forceinline__ void release_c(int lane) {
  if (lane == 0) mbar_arrive(st_empty(IT));
}
struct Ring {
  uint64_t dlo, dhi;
  uint32_t blo, bhi;
  uint32_t pe, po;
  __device__ __forceinline__ void set(int i, uint64_t d128) {
    const uint32_t f = i & 1;
    dlo = d128 + f * (4 * SLOT_BYTES / 16); dhi = d128 - f * (4 * SLOT_BYTES / 16);
    blo = f * 32; bhi = 0u - f * 32;
    pe = ((3 * i) >> 1) & 1; po = ((3 * i + 1) >> 1) & 1;
  }
  template <int V> __device__ __forceinline__ uint64_t wait() const {
    mbar_wait(A_FULL + 8 * (V & 7) + ((V & 4) ? bhi : blo), ((V & 4) ? po : pe) ^ ((V >> 3) & 1));
    return dadd<(V & 7) * (SLOT_BYTES / 16)>((V & 4) ? dhi : dlo);
  }
  template <int V> __device__ __forceinline__ void release(int lane) const {
    if (lane == 0) mbar_arrive(A_EMPTY + 8 * (V & 7) + ((V & 4) ? bhi : blo));
  }
};

__device__ __forceinline__ void ln_coef(float sum, float sq, float mul, uint32_t& sc, uint32_t& of) {
  const float m = sum * (1.f / D_);
  const float rs = mul * rsq(fmaxf(sq * (1.f / D_) - m * m, 0.f) + 1e-5f);
  sc = pack2(rs, rs);
  const float o = -m * bf_lo(sc);
  of = pack2(o, o);
}
template <int HI, int NEG>
__device__ __forceinline__ void softmax_exp(const float (&p)[36], float (&e)[18]) {
  constexpr float L2E = NEG ? -1.4426950408889634f : 1.4426950408889634f;
  float m = p[2 * HI];
#pragma unroll
  for (int i = 1; i < 18; i++) { const float v = p[4 * (i >> 1) + 2 * HI + (i & 1)]; m = NEG ? fminf(m, v) : fmaxf(m, v); }
  m *= -L2E;
#pragma unroll
  for (int i = 0; i < 18; i++) e[i] = ex2(fmaf(p[4 * (i >> 1) + 2 * HI + (i & 1)], L2E, m));
}
__device__ __forceinline__ void softmax_norm(const float (&e)[18], uint32_t (&w)[9]) {
  float s0 = e[0] + e[1], s1 = e[2] + e[3], s2 = e[4] + e[5];
#pragma unroll
  for (int i = 6; i < 18; i += 3) { s0 += e[i]; s1 += e[i + 1]; s2 += e[i + 2]; }
  const float s = rcp(s0 + s1 + s2);
#pragma unroll
  for (int t = 0; t < 9; t++) w[t] = pack2(e[2 * t] * s, e[2 * t + 1] * s);
}
template <int HI, int NEG>
__device__ __forceinline__ void softmax18(const float (&p)[36], uint32_t (&w)[9]) {
  float e[18];
  softmax_exp<HI, NEG>(p, e);
  softmax_norm(e, w);
}
template <int HI, int NEG>
__device__ __forceinline__ void phik_store(const float (&e)[18], uint32_t rowaddr, int c, int t7) {
  uint32_t w[9];
  softmax_norm(e, w);
  rowaddr += HI * 1024;
  sts128(rowaddr + ((((2 * NEG + 2 * c) & 7) ^ t7) << 4), w[0], w[1], w[2], w[3]);
  sts128(rowaddr + ((((2 * NEG + 1 + 2 * c) & 7) ^ t7) << 4), w[4], w[5], w[6], w[7]);
  sts32(rowaddr + ((((4 + 2 * c) & 7) ^ t7) << 4) + 4 * NEG, w[8]);
}
template <int HI, int NEG>
__device__ __forceinline__ void phik_piece(const float (&p)[36], uint32_t rowaddr, int c, int t7) {
  float e[18];
  softmax_exp<HI, NEG>(p, e);
  phik_store<HI, NEG>(e, rowaddr, c, t7);
}
template <int HI, int NEG>
__device__ __forceinline__ void phiq_piece(const float (&p)[36], uint32_t (&fq)[36]) {
  uint32_t w[9];
  softmax18<HI, NEG>(p, w);
#pragma unroll
  for (int t = 0; t < 8; t++) fq[2 * (8 * NEG + t) + HI] = w[t];
  fq[2 * (16 + NEG) + HI] = w[8];
}

template <class H>
__device__ __forceinline__ void phi_mma(float (&p)[36], const float (&acc)[32], uint32_t r0, uint32_t r1, uint64_t d, H hook) {
  uint32_t f[20];
#pragma unroll
  for (int j = 0; j < 16; j++) f[j] = pack2(acc[2 * j], acc[2 * j + 1]);
  f[16] = r0; f[17] = r1; f[18] = 0; f[19] = 0;
  wg_fence();
  static_for<0, 5>([&](auto s) { wgmma_rs<16, s.value != 0>(p, f[4 * s.value], f[4 * s.value + 1], f[4 * s.value + 2], f[4 * s.value + 3], d); });
  wg_commit();
  hook();
  wg_wait<0>(); pin(p);
}

__device__ __forceinline__ uint32_t nz(uint32_t w) { return w ? w : 0x8000u; }
__device__ __forceinline__ void stage_piece(uint32_t st, int lane, int odd, const uint32_t (&f)[16], uint32_t s0, uint32_t s1) {
  const uint32_t pf = st + odd * 256 + lane * 16;
#pragma unroll
  for (int s = 0; s < 4; s++) sts128(pf + s * 512, nz(f[4 * s]), f[4 * s + 1], f[4 * s + 2], f[4 * s + 3]);
  sts64(st + (odd ? 0 : 2048) + lane * 8, nz(s0), s1);
}
template <int C>
__device__ __forceinline__ void land_read(uint32_t (&a)[144], uint32_t base, int lane) {
  static_for<6 * C, 6 * C + 6>([&](auto s) {
    constexpr int k = s.value;
    constexpr uint32_t o = (C - 1) * 12288 + (k - 6 * C) * 512;
    if constexpr (k % 9 == 4) { lds64(base + o + lane * 8, a[4 * k], a[4 * k + 1]); lds64(base + o + 256 + lane * 8, a[4 * k + 2], a[4 * k + 3]); }
    else lds128(base + o + lane * 16, a[4 * k], a[4 * k + 1], a[4 * k + 2], a[4 * k + 3]);
  });
}
template <int C>
__device__ __forceinline__ void l2_read(uint32_t (&a)[144], const uint4* blk, int lane) {
  static_for<6 * C, 6 * C + 6>([&](auto s) {
    constexpr int k = s.value;
    if constexpr (k % 9 == 4) {
      const uint2* p = reinterpret_cast<const uint2*>(blk + k * 32) + lane;
      ldg64(p, a[4 * k], a[4 * k + 1]); ldg64(p + 32, a[4 * k + 2], a[4 * k + 3]);
    } else ldg128(blk + k * 32 + lane, a[4 * k], a[4 * k + 1], a[4 * k + 2], a[4 * k + 3]);
  });
}
template <int C>
__device__ __forceinline__ bool missing(const uint32_t (&a)[144], uint32_t thr) {
  constexpr int k = 6 * C, ks = (C == 0) ? 4 : (C == 2) ? 13 : (C == 3) ? 22 : (C == 5) ? 31 : -1;
  uint32_t m = __vimin3_u32(a[4 * k], a[4 * k + 4], a[4 * k + 8]);
  const uint32_t n = __vimin3_u32(a[4 * k + 12], a[4 * k + 16], a[4 * k + 20]);
  if constexpr (ks >= 0) m = __vimin3_u32(m, n, a[4 * (ks < 0 ? 0 : ks) + 2]); else m = min(m, n);
  return __any_sync(0xffffffffu, m < thr);
}
template <int C>
__device__ __forceinline__ void refetch(uint32_t (&a)[144], const uint4* blk, int lane, uint32_t thr) {
#pragma unroll 1
  do {
    l2_read<C>(a, blk, lane);
  } while (missing<C>(a, thr));
}

constexpr float GAMMA = 0.3292034911525734f, GELU_C = 2.423681954311584f, GELU_INV = 1.5188174288475842f;
template <int Q, int S>
__device__ __forceinline__ void gelu_step(const float (&y)[32], float (&t)[8], uint32_t dst) {
  if constexpr (S == 0) {
#pragma unroll
    for (int e = 0; e < 8; e++) t[e] = fmaf(y[8 * Q + e], y[8 * Q + e], GELU_C);
#pragma unroll
    for (int e = 0; e < 2; e++) t[e] *= y[8 * Q + e];
  } else if constexpr (S == 1) {
#pragma unroll
    for (int e = 2; e < 8; e++) t[e] *= y[8 * Q + e];
#pragma unroll
    for (int e = 0; e < 3; e++) t[e] = tanh_(t[e]);
  } else if constexpr (S == 2) {
#pragma unroll
    for (int e = 3; e < 8; e++) t[e] = tanh_(t[e]);
#pragma unroll
    for (int e = 0; e < 3; e++) t[e] = fmaf(y[8 * Q + e], t[e], y[8 * Q + e]);
  } else {
#pragma unroll
    for (int e = 3; e < 8; e++) t[e] = fmaf(y[8 * Q + e], t[e], y[8 * Q + e]);
    sts128(dst + Q * 512, pack2(t[0], t[1]), pack2(t[2], t[3]), pack2(t[4], t[5]), pack2(t[6], t[7]));
  }
  if constexpr (S < 3) pin(t);
}
template <int Q>
__device__ __forceinline__ void out_step(const float (&y)[32], uint32_t st, int lane) {
  const uint32_t ra = st + ((lane & 7) + (lane & 8)) * 128 + (((2 * Q) ^ (lane & 7) ^ (lane >> 4)) << 4);
  const float* v = &y[8 * Q];
  asm volatile("stmatrix.sync.aligned.m8n8.x4.shared.b16 [%0], {%1,%2,%3,%4};" ::"r"(ra),
               "r"(pack2(v[0] * GELU_INV, v[1] * GELU_INV)), "r"(pack2(v[2] * GELU_INV, v[3] * GELU_INV)),
               "r"(pack2(v[4] * GELU_INV, v[5] * GELU_INV)), "r"(pack2(v[6] * GELU_INV, v[7] * GELU_INV)) : "memory");
}
__device__ __forceinline__ void out_send(const CUtensorMap* m, uint32_t st, int col, int row, int lane) {
  fence_async_smem();
  __syncwarp();
  if (elect()) {
    asm volatile("cp.reduce.async.bulk.tensor.2d.global.shared::cta.add.tile.bulk_group [%0, {%2, %3}], [%1];" ::"l"(m), "r"(st), "r"(col), "r"(row) : "memory");
    bulk_commit();
    asm volatile("cp.async.bulk.wait_group.read 6;" ::: "memory");
  }
}
__device__ __forceinline__ int out_col(int q, int g) { const int b = q + g; return 64 * (b >= 9 ? b - 9 : b); }
template <int V0, int J0, int J1, class H>
__device__ __forceinline__ void ffn_pairs(float (&X)[32], float (&Y)[32], float (&t)[8], const uint32_t (&a)[144], uint64_t& d, const Params& P,
                                          int p, int g, const Ring& R, uint32_t slot, int row, int lane, H hook) {
  static_for<J0, J1>([&](auto jj) {
    constexpr int j = jj.value;
    if constexpr (j % 3 == 0) {
      d = R.template wait<V0 + j / 3>();
    }
    if constexpr (j == 0) {
      if (p <= 8) { wg_fence(); wgmma_init(X, P.dba, P.dbb + p * 8); wg_commit(); }
      wg_fence();
      wgmma_rp<128>(X, a[0], a[1], a[2], a[3], d, p <= 8);
    } else {
      wg_fence();
      wgmma_rs<128, 1>(X, a[8 * j], a[8 * j + 1], a[8 * j + 2], a[8 * j + 3], d);
    }
    wgmma_rs<128, 1>(X, a[8 * j + 4], a[8 * j + 5], a[8 * j + 6], a[8 * j + 7], d);
    wg_commit();
    if constexpr (j == 1) { wg_wait<2>(); pin(Y); R.template release<V0 - 1>(lane); }
    if constexpr (j % 3 == 2 && j > 2) { wg_wait<(J0 == 17) ? 1 : 3>(); R.template release<V0 + j / 3 - 1>(lane); }
    if constexpr (j >= 1 && j <= 16) {
      if (p <= 9) gelu_step<(j - 1) / 4, (j - 1) % 4>(Y, t, slot + lane * 16);
      else {
        if constexpr (j <= 4) out_step<j - 1>(Y, slot, lane);
        if constexpr (j == 6) out_send(&P.tout, slot, out_col(p - 10, g), row, lane);
      }
    }
    hook(jj);
  });
}

__global__ void __launch_bounds__(384, 1) fused_block_kernel(const __grid_constant__ Params P) {
  extern __shared__ __align__(1024) uint8_t smem_raw[];
  if (threadIdx.x == 0) asm volatile("prefetch.tensormap [%0];" ::"l"(&P.tx) : "memory");
  if ((uint32_t)__cvta_generic_to_shared(smem_raw) != SB) return;
  const int tid = threadIdx.x, warp = __shfl_sync(0xffffffffu, tid >> 5, 0), lane = __shfl_sync(0xffffffffu, tid & 31, tid & 31);
  const int blk = blockIdx.x;
  const int r = (blk >> 2) & 15, g = 4 * (blk >> 6) + (blk & 3);
  const int odd = g & 1;

  if (warp >= 8) {
    asm volatile("setmaxnreg.dec.sync.aligned.u32 24;");
    if (warp == 8) {
      if (elect()) {
#pragma unroll
        for (int q = 0; q < 14; q++) mbar_init(A_FULL + 8 * q, q < 10 ? 1 : 8);
#pragma unroll
        for (int q = 0; q < 10; q++) mbar_init(A_EMPTY + 8 * q, 8);
#pragma unroll
        for (int q = 0; q < 6; q++) mbar_init(A_PREP + 8 * q, q < 3 ? 96 : q == 5 ? 4 : q == 3 ? 2 : 1);
        fence_async_smem();
      }
      __syncwarp();
      bar_sync<BAR_INIT, 384>();
      uint32_t s8 = 0, par = 1, wrap = 80;
      auto issue = [&](const CUtensorMap* m, int c0, int c1, uint32_t bytes) {
        mbar_wait(A_EMPTY + s8, par);
        tma2d_e(SB + s8 * (SLOT_BYTES / 8) + (s8 >= 64 ? A_E - A_X : 0), m, c0, c1, A_FULL + s8, bytes);
        s8 += 8;
        if (s8 == wrap) { s8 = 0; wrap = 64; par ^= 1; }
      };
#pragma unroll 1
      for (int sec = 0; sec < 3; sec++) {
        const int cs = (sec == 2 ? 0 : (sec + 1) * D_) + 72 * g + 8 * odd;
#pragma unroll 1
        for (int s = 0; s < 6; s++) issue(&P.tq64, cs, 96 * s, SLOT_BYTES);
        if (sec == 0) {
#pragma unroll
          for (int s = 0; s < 3; s++) {
            if (s != 1) mbar_wait(A_XC + 4 * s, 0);
            tma3d_e(st_addr(6 + s), &P.tq8, 72 * g + (odd ? 0 : 64), 192 * s, 0, st_full(6 + s), 9216);
          }
          s8 = 72;
        }
      }
#pragma unroll 1
      for (int s = 0; s < 6; s++) issue(&P.to64, 72 * g + 8 * odd, 96 * s, SLOT_BYTES);
      mbar_wait(st_empty(ST_WO + 6), st_par(ST_WO + 6) ^ 1);
      tma3d_e(st_addr(ST_WO + 6), &P.to8, 72 * g + (odd ? 0 : 64), 0, 0, st_full(ST_WO + 6), 9216);
      static_assert((st_virt(ST_WO + 6) & 7) != 7, "no wrap here");
      s8 += 8;
#pragma unroll 1
      for (int p = 0; p < 18; p++) {
        const CUtensorMap* m = p < 9 ? &P.tw1 : &P.tw2;
        const int c0 = p < 9 ? D_ * g + 64 * p : out_col(p - 9, g), c1 = p < 9 ? 0 : D_ * g;
#pragma unroll 1
        for (int s = 0; s < 6; s++) issue(m, c0, c1 + 96 * s, SLOT_BYTES);
      }
    } else {
      const int ht = tid - 288, hw = warp - 9;
      const uint32_t lb = A_LAND + hw * 40, H = A_X + hw * 65536;
      if (hw == 0) {
        if (elect()) {
#pragma unroll
          for (int i = 0; i < 10; i++) mbar_init(A_LAND + 8 * i, 1);
          fence_async_smem();
          mbar_arrive(A_LAND + 72);
        }
        __syncwarp();
#pragma unroll
        for (int i = 0; i < 9; i++) tma2d_e(x_block(i), &P.tx, 64 * i, r * 128, A_LAND + 8 * i, 16384);
      }
      if (ht == 64) l2_prefetch(reinterpret_cast<const char*>(P.wqkv) + blk * 15552, 15552);
      const unsigned ep1 = ldg32(&g_epoch[blk]) + 1;
      uint32_t wv[7], bv[3];
      {
        const uint32_t* wp = reinterpret_cast<const uint32_t*>(P.wphi) + g * 648 + ht;
#pragma unroll
        for (int i = 0; i < 7; i++) if (i < 6 || ht < 72) wv[i] = ldg32(wp + 96 * i);
        const uint32_t* bp = reinterpret_cast<const uint32_t*>(P.b1) + g * 288 + ht;
#pragma unroll
        for (int i = 0; i < 3; i++) bv[i] = ldg32(bp + 96 * i);
      }
      bar_sync<BAR_INIT, 384>();
#pragma unroll
      for (int i = 0; i < 3; i++) sts32(A_B1 + ht * 4 + i * 384, bv[i]);
      sts32(A_B1 + 1152 + ht * 4, (ht < 32 || (ht & 3)) ? 0u : (ht < 64 ? 0x3ea9u : 0xba65u));
      if (ht < 54) g_kv[g * 864 + r * 54 + ht] = make_float4(0.f, 0.f, 0.f, 0.f);
      if (ht == 95) sts32(A_TGT, ep1 * 32);
      if (ht < 36) {
        const int j = ht >> 2, col = (j < 8 ? 8 * (j + odd) : (odd ? 0 : 64)) + 2 * (ht & 3);
        const int h = col / 18, d = col - 18 * h;
        sts32(A_VTAB + (ht & 3) * 48 + j * 4, A_V + h * 6144 + (d / 6) * 2048 + (d % 6) * 2);
      }
      mbar_wait(A_XC + 16, 0);
#pragma unroll 1
      for (int i = ht; i < 720; i += 96) sts128(A_WPHI + i * 16, 0, 0, 0, 0);
      bar_sync<BAR_HELP, 96>();
      {
#pragma unroll
        for (int i = 0; i < 7; i++) {
          const int e = ht + 96 * i, col = e / 9, t = e - col * 9, h = col / 18;
          const int kk = (odd && col < 8) ? 64 + col : col - 8 * odd;
          if (i < 6 || ht < 72) sts32(A_WPHI + t * 1280 + kk * 16 + 4 * h, wv[i]);
        }
      }
      fence_async_smem();
      mbar_arrive(A_PREP);
      mbar_wait(A_XC + 24, 0);
#pragma unroll 1
      for (int i = ht; i < 1536; i += 96) sts32(A_V + i * 16 + 12, 0x00003f80u);
      fence_async_smem();
      mbar_arrive(A_PREP + 8);
      if (ht == 64) l2_prefetch(reinterpret_cast<const char*>(P.wo) + blk * 5184, 5184);
      if (hw == 0) {
        if (elect()) signal_release(&g_cnt[g * 32]);
        __syncwarp();
        poll(&g_cnt[g * 32], ep1 * 16);
        asm volatile("fence.acq_rel.gpu;" ::: "memory");
        mbar_arrive(A_PREP + 16);
        bar_sync<BAR_KVOUT, 288>();
        tma2d_e(A_PHI + 12288, &P.txr, 72 * g, 128 * r, A_XR, 9216);
        tma2d_e(A_V + 12288, &P.txr, 72 * g, 128 * r + 64, A_XR, 9216);
      }
      else {
        mbar_wait(A_EEMPTY, 0); mbar_wait(A_EEMPTY + 8, 0);
        if (ht == 65) l2_prefetch(reinterpret_cast<const char*>(P.w1) + blk * 41472, 41472);
#pragma unroll
        for (int i = 0; i < 25; i++) sts128(A_KVB + (ht - 32) * 16 + i * 1024, 0, 0, 0, 0);
        fence_async_smem();
        mbar_arrive(A_PREP + 16);
      }
      if (hw < 2) {
        if (hw == 1) bar_sync<BAR_OMMA, 160>();
        __syncwarp();
#pragma unroll 1
        for (int x = 0; x < 2; x++) {
          poll(&g_cnt[(8 + 32 * x + 2 * r + hw) * 32], ep1 * 32);
          __syncwarp();
#pragma unroll
          for (int i = 0; i < 5; i++) tma3d_e(H + i * 12288, &P.tgx, 0, 2 * (i + 1), 128 * x + r * 8 + hw * 4, lb + 8 * i, 12288);
        }
      }
      bar_sync<BAR_HDONE, 352>();
      if (ht == 66) l2_prefetch(reinterpret_cast<const char*>(P.w2) + blk * 41472, 41472);
#pragma unroll 1
      for (int u = hw; u < 18; u += 3) {
        const int j = u >> 1, w0 = r * 8 + (u & 1) * 4, J = 9 * g + j;
        const bool split = (j == (odd ? 0 : 8));
        const uint2* src = reinterpret_cast<const uint2*>(g_h + (w0 * 36 + (J >> 1)) * 32) + (split ? (J & 1) * 32 + lane : (J & 1) + 2 * lane);
        const int col = 8 * J + 2 * (lane & 3);
        const uint32_t b = ldg32(P.b2 + col);
        uint32_t v[8];
#pragma unroll
        for (int w = 0; w < 4; w++) ldg64(src + w * 2304, v[2 * w], v[2 * w + 1]);
        __nv_bfloat16* o = P.out + (size_t)(w0 * 16 + (lane >> 2)) * D_ + col;
#pragma unroll
        for (int w = 0; w < 8; w++) stg32(o + w * 8 * D_, hadd2(v[w], b));
      }
      bar_sync<BAR_HELP, 96>();
      if (ht == 0) { signal_release(&g_cnt[(72 + r) * 32]); g_epoch[blk] = ep1; }
      __syncwarp();
      const uint32_t done = poll(&g_cnt[(72 + r) * 32], ep1 * 8);
      asm volatile("fence.acq_rel.gpu;" ::: "memory");
      if (ht == 0) mbar_arrive(A_OUTRDY);
      if (done) {
        const uint4 zero = make_uint4(0, 0, 0, 0);
#pragma unroll 1
        for (int i = 0; i < 16; i++) {
          uint4* p = g_x + ((i >> 3) * 128 + r * 8 + (i & 7)) * 1152 + g * 144 + ht;
          p[0] = zero;
          if (ht < 48) p[96] = zero;
        }
        if (ht < 64) reinterpret_cast<uint4*>(g_stats)[(r * 8 + (ht >> 3)) * 64 + g * 8 + (ht & 7)] = zero;
      }
    }
  } else {
    asm volatile("setmaxnreg.inc.sync.aligned.u32 240;");
    const int c = lane & 3, rq = lane >> 2, wg = warp >> 2, wq = warp & 3;
    const uint32_t lb = A_LAND + wg * 40;
    uint32_t a[144];
    uint32_t sl, ol, sh, oh;
    bar_sync<BAR_INIT, 384>();
    {
      const uint32_t xr = (warp * 16 + (lane & 15)) * 128;
      const int x7 = (lane & 7) ^ (lane >> 4);
      float sm[2][4] = {}, dl[2][4] = {}, dh[2][4] = {};
      static_for<0, 36>([&](auto s) {
        constexpr int k = s.value;
        if constexpr (k % 4 == 0) {
          constexpr int b = k / 4;
          if constexpr (b == 1 || b == 3 || b == 4) { if (lane == 0) mbar_arrive(A_XC + 8 * (b / 2)); }
          mbar_wait(A_LAND + 8 * b, 0);
          static_for<k, k + 4>([&](auto t) {
            constexpr int u = t.value;
            ldsm4(xr + x_block(b) + (((2 * (u & 3)) ^ x7) << 4), a[4 * u], a[4 * u + 1], a[4 * u + 2], a[4 * u + 3]);
          });
        }
        mma16816(sm[k & 1], a[4 * k], a[4 * k + 1], a[4 * k + 2], a[4 * k + 3], 0x3f803f80u, 0x3f803f80u);
        mma1688(dl[0], a[4 * k], a[4 * k + 1], a[4 * k]);
        mma1688(dh[0], a[4 * k], a[4 * k + 1], a[4 * k + 1]);
        mma1688(dl[1], a[4 * k + 2], a[4 * k + 3], a[4 * k + 2]);
        mma1688(dh[1], a[4 * k + 2], a[4 * k + 3], a[4 * k + 3]);
      });
      if (lane == 0) mbar_arrive(A_XC + 24);
      float ql = (rq & 1) ? dl[0][1] + dl[1][1] : dl[0][0] + dl[1][0];
      float qh = (rq & 1) ? dh[0][3] + dh[1][3] : dh[0][2] + dh[1][2];
      ql = __shfl_sync(0xffffffffu, ql, (lane & 28) | (rq >> 1));
      qh = __shfl_sync(0xffffffffu, qh, (lane & 28) | (rq >> 1));
      ln_coef(sm[0][0] + sm[1][0], ql, 1.f, sl, ol);
      ln_coef(sm[0][2] + sm[1][2], qh, 1.f, sh, oh);
    }
#pragma unroll
    for (int i = 0; i < 144; i++) { a[i] = (i & 1) ? hfma2(a[i], sh, oh) : hfma2(a[i], sl, ol); asm volatile("" : "+r"(a[i])); }
    uint32_t fq[36], xr[18];
    {
      float acc[32], p[36];
      uint32_t rq0, rq1;
      const uint32_t vrow = (warp * 16 + rq) * 16;
      {
        float r24[12], ka[32];
        uint32_t f[20];
        stage_c<6, 0, 128, 0>(ka, a, P.dq[0]);
        stage_c<6, 6, 128, 1>(ka, a, P.dq[0]);   wg_wait<1>(); release_c<0>(lane);
        stage_c<6, 12, 128, 2>(ka, a, P.dq[0]);  wg_wait<1>(); release_c<1>(lane);
        stage_c<6, 18, 128, 3>(ka, a, P.dq[0]);  wg_wait<1>(); release_c<2>(lane);
        stage_c<6, 24, 128, 4>(ka, a, P.dq[0]);  wg_wait<1>(); release_c<3>(lane);
        stage_c<6, 30, 128, 5>(ka, a, P.dq[0]);  wg_wait<1>(); release_c<4>(lane);
        stage_c<12, 0, 16, 6>(r24, a, P.d8);     wg_wait<1>(); pin(ka); release_c<5>(lane);
        stage_c<12, 12, 16, 7>(r24, a, P.d8);
#pragma unroll
        for (int j = 0; j < 16; j++) f[j] = pack2(ka[2 * j], ka[2 * j + 1]);
        stage_c<12, 24, 16, 8>(r24, a, P.d8);
        mbar_wait(A_PREP, 0);
        mbar_wait(A_PREP + 8, 0);
        uint32_t vt8;
        asm volatile("ld.shared.b32 %0, [%1];" : "=r"(vt8) : "r"(A_VTAB + c * 48 + 32) : "memory");
        wg_wait<0>(); pin(r24); release_c<6>(lane); release_c<7>(lane); release_c<8>(lane);
        f[16] = pack2(r24[4], r24[5]); f[17] = pack2(r24[6], r24[7]); f[18] = 0; f[19] = 0;
        sts64(A_X + 129024 + warp * 256 + lane * 8, pack2(r24[0], r24[1]), pack2(r24[2], r24[3]));
        sts32(vt8 + vrow, pack2(r24[8], r24[9]));
        sts32(vt8 + vrow + 128, pack2(r24[10], r24[11]));
        sched_fence();
        uint64_t d = P.dwphi;
        wg_fence();
        static_for<0, 5>([&](auto s) { wgmma_rs<16, s.value != 0>(p, f[4 * s.value], f[4 * s.value + 1], f[4 * s.value + 2], f[4 * s.value + 3], d); });
        wg_commit();
        wg_wait<0>(); pin(p);
      }
      const uint32_t prow = A_PHI + c * 16384 + (warp * 16 + rq) * 128;
      phik_piece<0, 0>(p, prow, c, rq);
      sched_fence();
      float sm_e[18];
      stage_c<6, 0, 128, 9>(acc, a, P.dq[1]);
      softmax_exp<0, 1>(p, sm_e);        sched_fence();
      stage_c<6, 6, 128, 10>(acc, a, P.dq[1]);  wg_wait<1>(); release_c<9>(lane);
      phik_store<0, 1>(sm_e, prow, c, rq); sched_fence();
      stage_c<6, 12, 128, 11>(acc, a, P.dq[1]); wg_wait<1>(); release_c<10>(lane);
      softmax_exp<1, 0>(p, sm_e);        sched_fence();
      stage_c<6, 18, 128, 12>(acc, a, P.dq[1]); wg_wait<1>(); release_c<11>(lane);
      phik_store<1, 0>(sm_e, prow, c, rq); sched_fence();
      stage_c<6, 24, 128, 13>(acc, a, P.dq[1]); wg_wait<1>(); release_c<12>(lane);
      softmax_exp<1, 1>(p, sm_e);        sched_fence();
      stage_c<6, 30, 128, 14>(acc, a, P.dq[1]); wg_wait<1>(); release_c<13>(lane);
      phik_store<1, 1>(sm_e, prow, c, rq);
      uint32_t vt[8];
      lds128(A_VTAB + c * 48, vt[0], vt[1], vt[2], vt[3]);
      lds128(A_VTAB + c * 48 + 16, vt[4], vt[5], vt[6], vt[7]);
      float qa[32];
      stage_c<4, 0, 128, 15>(qa, a, P.dq[2]);
      wg_wait<1>(); pin(acc); release_c<14>(lane);
#pragma unroll
      for (int j = 0; j < 8; j++) {
        sts32(vt[j] + vrow, pack2(acc[4 * j], acc[4 * j + 1]));
        sts32(vt[j] + vrow + 128, pack2(acc[4 * j + 2], acc[4 * j + 3]));
      }
      fence_async_smem();
      bar_sync<BAR_KVIN, 256>();
      float kv0[12], kv1[12];
      {
        uint64_t da = P.dphi + wg * 2048, db = P.dv + wg * 768;
        wg_fence();
        static_for<0, 8>([&](auto s) { wgmma_ss_tt<128, s.value == 7 ? 384 - 112 : 16, s.value != 0>(kv0, da, db); });
        wg_commit();
        static_for<0, 8>([&](auto s) { wgmma_ss_tt<128, 16, s.value != 0>(kv1, da, db); });
        wg_commit();
      }
      mbar_wait(A_PREP + 16, 0);
      fence_async_global();
      static_for<0, 2>([&](auto hc) {
        constexpr int hh = hc.value;
        float (&kvp)[12] = hh ? kv1 : kv0;
        wg_wait<1 - hh>(); pin(kvp);
        bar_sync_wg(wg);
        const int f0 = 8 * ((2 * wq - 4 * wg - 2 * hh) & 7);
        const uint32_t sa = A_V + (2 * wg + hh) * 6144 + f0 * 96;
#pragma unroll
        for (int u2 = 0; u2 < 2; u2++) {
          if (f0 + 8 * u2 + rq < 36) {
#pragma unroll
            for (int j = 0; j < 3; j++)
              sts64(sa + (8 * u2 + rq) * 96 + c * 8 + 32 * j, __float_as_uint(kvp[4 * j + 2 * u2]), c == 3 ? 0x3f800000u : __float_as_uint(kvp[4 * j + 2 * u2 + 1]));
          }
        }
        fence_async_smem();
        __syncwarp();
        if (f0 < 36 && elect())
          asm volatile("cp.reduce.async.bulk.global.shared::cta.bulk_group.add.f32 [%0], [%1], %2;"
                       ::"l"(g_kv + g * 864 + (2 * wg + hh) * 216 + f0 * 6), "r"(sa), "r"(f0 < 32 ? 1536 : 384) : "memory");
      });
      bulk_commit();
      if (wg) bulk_wait_all();
      __syncwarp();
      bar_arrive<BAR_KVOUT, 288>();
      if (wg) {
        const int fl = lane / 6, pt = lane - 6 * fl, n0 = 18 * wq + 6 * (pt >> 1) + 4 * (pt & 1), n1 = n0 + 2;
        const uint32_t ra = A_KVB + (8 * (fl >> 1) + (fl & 1) + 2 * wq) * 16;
        const uint32_t d0 = ra + (n0 >> 3) * 2304 + (n0 & 7) * 2;
        const uint32_t d1 = (pt & 1) ? ra + (9 + (wq >> 1)) * 2304 : ra + (n1 >> 3) * 2304 + (n1 & 7) * 2;
        uint32_t kvr[9][4];
        const float4* kv = g_kv + g * 864 + wq * 216 + (lane < 24 ? lane : lane - 8);
        bar_sync<BAR_T0, 256>();
#pragma unroll 1
        for (int n = 0; n < SPIN_LIMIT; n++) {
#pragma unroll
          for (int u = 0; u < 9; u++)
            ldg128(kv + u * 24, kvr[u][0], kvr[u][1], kvr[u][2], kvr[u][3]);
          bool ok = true;
#pragma unroll
          for (int u = 0; u < 9; u++) ok = ok && (!(lane & 1) || kvr[u][3] == 0x41800000u);
          if (__all_sync(0xffffffffu, ok)) break;
        }
        if (lane < 24) {
#pragma unroll
          for (int u = 0; u < 9; u++) sts32(d0 + u * 256, pack2(__uint_as_float(kvr[u][0]), __uint_as_float(kvr[u][1])));
          if (!(pt & 1)) {
#pragma unroll
            for (int u = 0; u < 9; u++) sts32(d1 + u * 256, pack2(__uint_as_float(kvr[u][2]), __uint_as_float(kvr[u][3])));
          } else if (pt == 1) {
#pragma unroll
            for (int u = 0; u < 9; u++) {
              const uint32_t zz = (wq & 1) ? pack2(0.f, __uint_as_float(kvr[u][2])) : pack2(__uint_as_float(kvr[u][2]), 0.f);
              sts128(d1 + u * 256, zz, zz, zz, zz);
            }
          }
        }
        fence_async_smem();
        __syncwarp();
        if (lane == 0) mbar_arrive(A_KVRDY);
        bar_sync<BAR_T1, 256>();
      }
      stage_issue<2, 4, 128, 0>(qa, a, dadd<(st_addr(15) - SB) / 16 + 4 * 128>(P.dq[2]));
      stage_c<6, 6, 128, 16>(qa, a, P.dq[2]);   wg_wait<1>(); release_c<15>(lane);
      stage_c<6, 12, 128, 17>(qa, a, P.dq[2]);  wg_wait<1>(); release_c<16>(lane);
      stage_c<6, 18, 128, 18>(qa, a, P.dq[2]);  wg_wait<1>(); release_c<17>(lane);
      stage_c<6, 24, 128, 19>(qa, a, P.dq[2]);  wg_wait<1>(); release_c<18>(lane);
      stage_c<6, 30, 128, 20>(qa, a, P.dq[2]);  wg_wait<1>(); release_c<19>(lane);
      lds64(A_X + 129024 + warp * 256 + lane * 8, rq0, rq1);
      wg_wait<0>(); pin(qa); release_c<20>(lane);
      phi_mma(p, qa, rq0, rq1, P.dwphi2, [&] { if (!wg) bar_arrive<BAR_T0, 256>(); });
      phiq_piece<0, 0>(p, fq); phiq_piece<1, 0>(p, fq);
      phiq_piece<0, 1>(p, fq); phiq_piece<1, 1>(p, fq);
    }
    sched_fence();
    const int rw = r * 8 + warp;
    uint32_t tgt;
    asm volatile("ld.shared.b32 %0, [%1];" : "=r"(tgt) : "r"(A_TGT) : "memory");
    const uint32_t land = A_X + wg * 65536 + wq * 3072;
    {
      float o[44];
      uint64_t d = P.dkvb;
      mbar_wait(A_KVRDY, 0);
      wg_fence();
      static_for<0, 9>([&](auto s) { wgmma_rs<16, s.value != 0>(o, fq[4 * s.value], fq[4 * s.value + 1], fq[4 * s.value + 2], fq[4 * s.value + 3], d); });
      wg_commit();
      if (!wg) bar_arrive<BAR_T1, 256>();
      {
        mbar_wait(A_XR, 0);
        const uint32_t xa = A_X + wg * 65536 + 12288 + (wq * 16 + (lane & 15)) * 144;
#pragma unroll
        for (int j = 0; j < 4; j++) ldsm4(xa + (lane >> 4) * 16 + odd * 16 + j * 32, xr[4 * j], xr[4 * j + 1], xr[4 * j + 2], xr[4 * j + 3]);
        asm volatile("ldmatrix.sync.aligned.m8n8.x2.shared.b16 {%0,%1}, [%2];" : "=r"(xr[16]), "=r"(xr[17]) : "r"(xa + (odd ? 0 : 128)) : "memory");
      }
      wg_wait<0>(); pin(o);
      if (!wg) bar_arrive<BAR_OMMA, 160>();
      uint32_t f[18], ff[16];
#pragma unroll
      for (int u = 0; u < 2; u++) {
        const float i0 = rcp(o[36 + 2 * u] + 1e-6f), i1 = rcp(o[37 + 2 * u] + 1e-6f), i2 = rcp(o[40 + 2 * u] + 1e-6f), i3 = rcp(o[41 + 2 * u] + 1e-6f);
        const float sc[9] = {i0, i0, c < 1 ? i0 : i1, i1, c < 2 ? i1 : i2, i2, c < 3 ? i2 : i3, i3, i3};
#pragma unroll
        for (int j = 0; j < 9; j++) f[2 * j + u] = pack2(o[4 * j + 2 * u] * sc[j], o[4 * j + 2 * u + 1] * sc[j]);
      }
#pragma unroll
      for (int i = 0; i < 16; i++) ff[i] = odd ? f[i + 2] : f[i];
      stage_piece(land, lane, odd, ff, odd ? f[0] : f[16], odd ? f[1] : f[17]);
      fence_async_smem();
      __syncwarp();
      if (elect()) {
        bulk_store(reinterpret_cast<char*>(g_o + rw * 1152) + g * 2304, land, 2304);
        bulk_commit(); bulk_wait_all();
        signal(&g_cnt[(8 + 2 * r + wg) * 32]);
      }
    }
    {
      float h64[32], h8[4];
#pragma unroll
      for (int j = 0; j < 18; j++) {
        float* v = j < 16 ? &h64[2 * (j & 15)] : &h8[2 * (j & 1)];
        v[0] = bf_lo(xr[j]); v[1] = bf_hi(xr[j]);
      }
      pin(h64); pin(h8);
      __syncwarp();
      const uint32_t thr = poll(&g_cnt[(8 + 2 * r + wg) * 32], tgt);
      l2_read<0>(a, g_o + rw * 1152, lane);
      static_for<0, 7>([&](auto q) { mbar_wait(st_full(ST_WO + q.value), st_par(ST_WO + q.value)); });
      if (wg) bar_sync<BAR_T2, 256>();
      bool bad = false;
      static_for<0, 6>([&](auto cc) {
        constexpr int C = cc.value, ST = ST_WO + C;
        if constexpr (C == 1) { mbar_wait(lb, 1); land_read<1>(a, land, lane); }
        if constexpr (C >= 1 && C < 5) { mbar_wait(lb + 8 * C, 1); land_read<C + 1>(a, land, lane); }
        if constexpr (C < 2) bad = missing<C>(a, thr);
        if (__builtin_expect(bad, 0)) refetch<C>(a, g_o + rw * 1152, lane, thr);
        wg_fence();
        mma_run<6, 6 * C, 16, 1>(h8, a, dadd<(st_addr(ST_WO + 6) - SB) / 16 + C * 96>(P.d8o));
        mma_run<6, 6 * C, 128, 1>(h64, a, dadd<(st_addr(ST) - SB) / 16>(P.dq[3]));
        wg_commit();
        if constexpr (C == 5) { if (!wg) bar_arrive<BAR_T2, 256>(); }
        if constexpr (C >= 1 && C < 5) bad = missing<C + 1>(a, thr);
        if constexpr (C >= 2) { wg_wait<2>(); release_c<ST - 2>(lane); }
      });
      wg_wait<0>(); pin(h64); pin(h8); release_c<ST_WO + 4>(lane); release_c<ST_WO + 5>(lane); release_c<ST_WO + 6>(lane);
      uint32_t f[18];
#pragma unroll
      for (int j = 0; j < 9; j++) {
        const float* v = j < 8 ? &h64[4 * (j & 7)] : h8;
        f[2 * j] = pack2(v[0], v[1]);
        f[2 * j + 1] = pack2(v[2], v[3]);
      }
      stage_piece(land, lane, odd, reinterpret_cast<const uint32_t(&)[16]>(f), f[16], f[17]);
      fence_async_smem();
      __syncwarp();
      if (elect()) { bulk_store(reinterpret_cast<char*>(g_h + rw * 1152) + g * 2304, land, 2304); bulk_commit(); }
      sched_fence();
      float sl, ql, sh, qh;
      {
        float s4[4], q4[4];
#pragma unroll
        for (int e = 0; e < 4; e++) { s4[e] = h8[e]; q4[e] = h8[e] * h8[e]; }
#pragma unroll
        for (int j = 0; j < 32; j++) { s4[j & 3] += h64[j]; q4[j & 3] = fmaf(h64[j], h64[j], q4[j & 3]); }
        sl = s4[0] + s4[1]; ql = q4[0] + q4[1]; sh = s4[2] + s4[3]; qh = q4[2] + q4[3];
      }
      {
        float a0 = (c & 1) ? sl : ql, k0 = (c & 1) ? ql : sl, a1 = (c & 1) ? sh : qh, k1 = (c & 1) ? qh : sh;
        k0 += __shfl_xor_sync(0xffffffffu, a0, 1);
        k1 += __shfl_xor_sync(0xffffffffu, a1, 1);
        const float snd = (c & 2) ? k0 : k1;
        float kp = (c & 2) ? k1 : k0;
        kp += __shfl_xor_sync(0xffffffffu, snd, 2);
        asm volatile("st.relaxed.gpu.global.u32 [%0], %1;" ::"l"(reinterpret_cast<uint32_t*>(g_stats + rw * 64 + g * 8) + lane), "r"(__float_as_uint(kp) | ((c & 1) << 31)) : "memory");
      }
      if (elect()) {
        bulk_wait_all();
        signal(&g_cnt[(40 + 2 * r + wg) * 32]);
      }
    }
    float accA[32], accB[32];
    {
      __syncwarp();
      uint32_t s0, s1, s2, s3, t0, t1, t2, t3, thr;
      thr = poll(&g_cnt[(40 + 2 * r + wg) * 32], tgt);
      ldg128(g_stats + rw * 64 + c * 16 + rq, s0, s1, s2, s3);
      ldg128(g_stats + rw * 64 + c * 16 + 8 + rq, t0, t1, t2, t3);
      l2_read<0>(a, g_h + rw * 1152, lane);
      static_for<0, 4>([&](auto q) { mbar_wait(st_full(ST_FFN + q.value), st_par(ST_FFN + q.value)); });
#pragma unroll 1
      while (__builtin_expect(__any_sync(0xffffffffu, min(s1, t1) < thr), 0)) {
        ldg128(g_stats + rw * 64 + c * 16 + rq, s0, s1, s2, s3);
        ldg128(g_stats + rw * 64 + c * 16 + 8 + rq, t0, t1, t2, t3);
      }
      float sl = __uint_as_float(s0) + __uint_as_float(t0), ql = -__uint_as_float(s1) - __uint_as_float(t1);
      float sh = __uint_as_float(s2) + __uint_as_float(t2), qh = -__uint_as_float(s3) - __uint_as_float(t3);
#pragma unroll
      for (int m = 1; m < 4; m <<= 1) {
        sl += __shfl_xor_sync(0xffffffffu, sl, m); ql += __shfl_xor_sync(0xffffffffu, ql, m);
        sh += __shfl_xor_sync(0xffffffffu, sh, m); qh += __shfl_xor_sync(0xffffffffu, qh, m);
      }
      uint32_t cl, ol, ch, oh;
      ln_coef(sl, ql, GAMMA, cl, ol);
      ln_coef(sh, qh, GAMMA, ch, oh);
      auto center = [&](int k0) {
#pragma unroll
        for (int i = 4 * k0; i < 4 * k0 + 24; i++) a[i] = (i & 1) ? hfma2(a[i], ch, oh) : hfma2(a[i], cl, ol);
      };
      wg_fence(); wgmma_init(accA, P.dba, P.dbb);
      mbar_wait(lb, 0); land_read<1>(a, land, lane);
      if (__builtin_expect(missing<0>(a, thr), 0)) refetch<0>(a, g_h + rw * 1152, lane, thr);
      bool bad = missing<1>(a, thr);
      center(0);
      static_for<0, 6>([&](auto cc) {
        constexpr int C = cc.value, ST = ST_FFN + C;
        if constexpr (C >= 4) mbar_wait(st_full(ST), st_par(ST));
        if constexpr (C < 4) { mbar_wait(lb + 8 * C + 8, 0); land_read<C + 2>(a, land, lane); }
        if constexpr (C < 5) { if (__builtin_expect(bad, 0)) refetch<C + 1>(a, g_h + rw * 1152, lane, thr); }
        wg_fence();
        mma_run<C < 5 ? 6 : 4, 6 * C, 128, 1>(accA, a, dadd<(st_addr(ST) - SB) / 16>(P.dq[4]));
        wg_commit();
        if constexpr (C < 5) center(6 * C + 6);
        if constexpr (C < 4) bad = missing<C + 2>(a, thr);
        if constexpr (C >= 1 && C < 5) { wg_wait<1>(); release_c<ST - 1>(lane); }
      });
      bar_arrive<BAR_HDONE, 352>();
      bar_sync_wg(wg);
    }
    {
      const uint32_t xw = A_X + warp * 16384;
      const int grow = r * 128 + warp * 16;
      constexpr int VF = st_virt(ST_FFN);
      Ring R;
      uint64_t d = dadd<(st_addr(ST_FFN + 5) - SB) / 16 + 4 * 128>(P.d128);
      float t[8];
#pragma unroll 1
      for (int i = 0; i < 9; i++) {
        const uint32_t hd = xw + (i & 3) * 4096;
        R.set(i, P.d128);
        auto reload = [&](auto k0, auto k1) {
#pragma unroll
          for (int s = k0.value; s < k1.value; s++) lds128(xw + lane * 16 + (s & 31) * 512, a[4 * s], a[4 * s + 1], a[4 * s + 2], a[4 * s + 3]);
        };
        ffn_pairs<VF, 17, 18>(accA, accB, t, a, d, P, 2 * i, g, R, hd, grow, lane, [&](auto) {
          if (i == 4) { reload(ic<24>{}, ic<30>{}); }
        });
        ffn_pairs<VF + 6, 0, 18>(accB, accA, t, a, d, P, 2 * i + 1, g, R, hd, grow, lane, [&](auto jj) {
          if constexpr (jj.value == 8) { if (i == 8 && wg) bar_sync<BAR_T1, 256>(); }
          if constexpr (jj.value == 13) { if (i == 4) { reload(ic<30>{}, ic<35>{}); mbar_wait(A_OUTRDY, 0); fence_async_global(); } }
          if constexpr (jj.value == 16) { if (i == 4) { reload(ic<35>{}, ic<36>{}); } }
        });
        if (i < 8) ffn_pairs<VF + 12, 0, 17>(accA, accB, t, a, d, P, 2 * i + 2, g, R, hd + 2048, grow, lane, [&](auto jj) {
          if constexpr (jj.value % 3 == 2 && jj.value > 2) { if (i == 3) reload(ic<2 * jj.value - 10>{}, ic<2 * jj.value - 4>{}); }
        });
        else {
          if (!wg) bar_arrive<BAR_T1, 256>();
          wg_wait<0>(); pin(accB);
          out_step<0>(accB, xw + 2048, lane); out_step<1>(accB, xw + 2048, lane); out_step<2>(accB, xw + 2048, lane); out_step<3>(accB, xw + 2048, lane);
          out_send(&P.tout, xw + 2048, out_col(8, g), grow, lane);
        }
        asm volatile("" : "+r"(i));
      }
      wg_wait<0>();
      asm volatile("cp.async.bulk.wait_group.read 0;" ::: "memory");
    }
  }
}

typedef CUresult (*EncodeFn)(CUtensorMap*, CUtensorMapDataType, cuuint32_t, void*, const cuuint64_t*, const cuuint64_t*, const cuuint32_t*,
                             const cuuint32_t*, CUtensorMapInterleave, CUtensorMapSwizzle, CUtensorMapL2promotion, CUtensorMapFloatOOBfill);

void enc2d(EncodeFn fn, CUtensorMap* m, const void* base, uint64_t cols, uint64_t rows, uint32_t bc, uint32_t br) {
  cuuint64_t gd[2] = {cols, rows}, gs[1] = {cols * 2};
  cuuint32_t bd[2] = {bc, br}, es[2] = {1, 1};
  fn(m, CU_TENSOR_MAP_DATA_TYPE_BFLOAT16, 2, const_cast<void*>(base), gd, gs, bd, es, CU_TENSOR_MAP_INTERLEAVE_NONE,
     CU_TENSOR_MAP_SWIZZLE_128B, CU_TENSOR_MAP_L2_PROMOTION_L2_128B, CU_TENSOR_MAP_FLOAT_OOB_FILL_NONE);
}

}

extern "C" void kernel_launch(void* const* d_in, const int* in_sizes, int n_in, void* d_out, int out_size) {
  (void)in_sizes; (void)n_in; (void)out_size;
  static EncodeFn fn = nullptr;
  static void* px = nullptr;
  if (!fn) {
    void* p = nullptr;
    cudaDriverEntryPointQueryResult q;
    cudaGetDriverEntryPoint("cuTensorMapEncodeTiled", &p, cudaEnableDefault, &q);
    fn = (EncodeFn)p;
    cudaFuncSetAttribute(fused_block_kernel, cudaFuncAttributeMaxDynamicSharedMemorySize, SMEM_BYTES);
    cudaGetSymbolAddress(&px, g_x);
  }
  Params P;
  P.x = (const __nv_bfloat16*)d_in[0];
  P.wqkv = (const __nv_bfloat16*)d_in[1];
  P.wphi = (const __nv_bfloat16*)d_in[2];
  P.wo = (const __nv_bfloat16*)d_in[3];
  P.w1 = (const __nv_bfloat16*)d_in[5];
  P.b1 = (const __nv_bfloat16*)d_in[6];
  P.w2 = (const __nv_bfloat16*)d_in[7];
  P.b2 = (const __nv_bfloat16*)d_in[8];
  P.out = (__nv_bfloat16*)d_out;
  P.d128 = desc64(SB, 16, 1024, 1);
  P.dba = desc64(A_B1 + 1280, 128, 0, 0);
  P.dbb = desc64(A_B1, 0, 16, 0);
  P.d8 = desc64(SB, 128, 3072, 0);
  P.dwphi = desc64(A_WPHI, 128, 1280, 0);
  P.dkvb = desc64(A_KVB, 128, 2304, 0);
  P.dphi = desc64(A_PHI, 16, 1024, 1);
  P.dv = desc64(A_V, 128, 2048, 0);
  for (int i = 0; i < 5; i++) P.dq[i] = P.d128;
  P.d8o = P.d8;
  P.dwphi2 = P.dwphi;
  enc2d(fn, &P.tq64, P.wqkv, 3 * D_, D_, 64, 96);
  {
    cuuint64_t gd[3] = {(cuuint64_t)D_, (cuuint64_t)D_, 3}, gs[2] = {3 * D_ * 2, D_ * 2};
    cuuint32_t bd[3] = {8, 192, 3}, es[3] = {1, 1, 1};
    fn(&P.tq8, CU_TENSOR_MAP_DATA_TYPE_BFLOAT16, 3, const_cast<__nv_bfloat16*>(P.wqkv), gd, gs, bd, es, CU_TENSOR_MAP_INTERLEAVE_NONE,
       CU_TENSOR_MAP_SWIZZLE_NONE, CU_TENSOR_MAP_L2_PROMOTION_L2_128B, CU_TENSOR_MAP_FLOAT_OOB_FILL_NONE);
  }
  enc2d(fn, &P.to64, P.wo, D_, D_, 64, 96);
  {
    cuuint64_t gd[3] = {(cuuint64_t)D_, 192, 3}, gs[2] = {D_ * 2, 192 * D_ * 2};
    cuuint32_t bd[3] = {8, 192, 3}, es[3] = {1, 1, 1};
    fn(&P.to8, CU_TENSOR_MAP_DATA_TYPE_BFLOAT16, 3, const_cast<__nv_bfloat16*>(P.wo), gd, gs, bd, es, CU_TENSOR_MAP_INTERLEAVE_NONE,
       CU_TENSOR_MAP_SWIZZLE_NONE, CU_TENSOR_MAP_L2_PROMOTION_L2_128B, CU_TENSOR_MAP_FLOAT_OOB_FILL_NONE);
  }
  enc2d(fn, &P.tw1, P.w1, F_, D_, 64, 96);
  enc2d(fn, &P.tw2, P.w2, D_, F_, 64, 96);
  enc2d(fn, &P.tout, P.out, D_, S_, 64, 16);
  enc2d(fn, &P.tx, P.x, D_, S_, 64, 128);
  {
    cuuint64_t gd[3] = {192, 12, 256}, gs[2] = {1536, 18432};
    cuuint32_t bd[3] = {192, 2, 4}, es[3] = {1, 1, 1};
    fn(&P.tgx, CU_TENSOR_MAP_DATA_TYPE_UINT64, 3, px, gd, gs, bd, es, CU_TENSOR_MAP_INTERLEAVE_NONE,
       CU_TENSOR_MAP_SWIZZLE_NONE, CU_TENSOR_MAP_L2_PROMOTION_L2_128B, CU_TENSOR_MAP_FLOAT_OOB_FILL_NONE);
  }
  {
    cuuint64_t gd[2] = {(cuuint64_t)D_, (cuuint64_t)S_}, gs[1] = {D_ * 2};
    cuuint32_t bd[2] = {72, 64}, es[2] = {1, 1};
    fn(&P.txr, CU_TENSOR_MAP_DATA_TYPE_BFLOAT16, 2, const_cast<__nv_bfloat16*>(P.x), gd, gs, bd, es, CU_TENSOR_MAP_INTERLEAVE_NONE,
       CU_TENSOR_MAP_SWIZZLE_NONE, CU_TENSOR_MAP_L2_PROMOTION_L2_128B, CU_TENSOR_MAP_FLOAT_OOB_FILL_NONE);
  }
  fused_block_kernel<<<128, 384, SMEM_BYTES>>>(P);
}
```
